```python
import torch

def _softmax(x, axis=-1):
    return torch.softmax(x, dim=axis)

def _gelu(x):
    return torch.nn.functional.gelu(x, approximate='tanh')

def _silu(x):
    return torch.nn.functional.silu(x)

def _sigmoid(x):
    return torch.sigmoid(x)

def _layernorm(x, axis=-1, eps=1e-05):
    m = x.mean(dim=axis, keepdim=True)
    v = x.var(dim=axis, keepdim=True, unbiased=False)
    return (x - m) / torch.sqrt(v + eps)

def _scatter_add(tgt, idx, src, axis=0):
    return tgt.clone().index_add_(axis, idx, src)

def _segment_sum(src, seg, n):
    out = torch.zeros((n,) + src.shape[1:], dtype=src.dtype)
    return out.index_add_(0, seg, src)

def _pad(x, pw):
    flat = tuple((v for pair in reversed(pw) for v in pair))
    return torch.nn.functional.pad(x, flat)
kernel_name = 'adaLN_cond__sliding_block_cached__dense_activation_silu__prompt'

def setup_inputs():

    _w = lambda a: (lambda t: t.to(torch.bfloat16) if t.is_floating_point() else t)(torch.as_tensor(a))

    def _A_setup():
        B, Sq, D = (1, 2048, 512)
        Hq, Hkv, Sk, Dh = (32, 8, 2048, 128)
        assert Hq % Hkv == 0, (Hq, Hkv)
        return {'x': _w((lambda *s: torch.randn(*s, dtype=torch.bfloat16) * 0.05)(B, Sq, D)), 'k_cache': _w((lambda *s: torch.randn(*s, dtype=torch.bfloat16) * 1.6)(B, Hkv, Sk, Dh)), 'v_cache': _w((lambda *s: torch.randn(*s, dtype=torch.bfloat16) * 0.8)(B, Hkv, Sk, Dh)), 'wq': _w((lambda *s: torch.randn(*s, dtype=torch.bfloat16) * 1.6)(D, Hq * Dh) * D ** (-0.5)), 'wo': _w((lambda *s: torch.randn(*s, dtype=torch.bfloat16) * 0.8)(Hq * Dh, D) * (Hq * Dh) ** (-0.5))}
    _A_in = _A_setup()

    def _B_setup():
        B, S, D, F = (1, 2048, 512, 1792)
        return {'x': _w((lambda *s: torch.randn(*s, dtype=torch.bfloat16) * 0.05)(B, S, D)), 'w1': _w((lambda *s: torch.randn(*s, dtype=torch.bfloat16) * 1.6)(D, F) * D ** (-0.5)), 'w2': _w((lambda *s: torch.randn(*s, dtype=torch.bfloat16) * 0.2)(F, D) * F ** (-0.5))}
    _B_in = _B_setup()
    return {'A_x': _A_in['x'], 'A_k_cache': _A_in['k_cache'], 'A_v_cache': _A_in['v_cache'], 'A_wq': _A_in['wq'], 'A_wo': _A_in['wo'], 'B_x': _B_in['x'], 'B_w1': _B_in['w1'], 'B_w2': _B_in['w2'], 'c': _w((lambda *s: torch.randn(*s, dtype=torch.bfloat16) * 0.1)(1, 512) * 8.0), 'w_mod': _w((lambda *s: torch.randn(*s, dtype=torch.bfloat16) * 0.1)(512, 6 * 512) * 512 ** (-0.5) * 8.0)}

def reference(A_x, A_k_cache, A_v_cache, A_wq, A_wo, B_x, B_w1, B_w2, c, w_mod):

    def _A_ref(x, k_cache, v_cache, wq, wo):
        B, Sq, D = x.shape
        Hq, Dh = (32, 128)
        Hkv, Sk = (k_cache.shape[1], k_cache.shape[2])
        W = min(4096, max(256, Sk // 4))
        rep = Hq // Hkv
        q = (lambda x, *d: x.permute(*d))((x @ wq).reshape(B, Sq, Hq, Dh), 0, 2, 1, 3)
        k = (lambda x, n, axis: torch.repeat_interleave(x, n, dim=axis))(k_cache[:, :, Sk - W:, :], rep, axis=1)
        v = (lambda x, n, axis: torch.repeat_interleave(x, n, dim=axis))(v_cache[:, :, Sk - W:, :], rep, axis=1)
        scores = torch.einsum('bhqd,bhkd->bhqk', q, k) * Dh ** (-0.5)
        p = _softmax(scores, axis=-1)
        o = torch.einsum('bhqk,bhkd->bhqd', p, v)
        return (lambda x, *d: x.permute(*d))(o, 0, 2, 1, 3).reshape(B, Sq, Hq * Dh) @ wo

    def _B_ref(x, w1, w2):
        h = torch.einsum('bsd,df->bsf', x, w1)
        h = _silu(h)
        out = torch.einsum('bsf,fd->bsd', h, w2)
        return out
    x = A_x
    mod = (_silu(c) @ w_mod).reshape(c.shape[0], 6, 1, -1)
    sa, ca, ga, sb, cb, gb = (mod[:, 0].clone(), mod[:, 1].clone(), mod[:, 2].clone(), mod[:, 3].clone(), mod[:, 4].clone(), mod[:, 5].clone())
    h = _layernorm(x, axis=-1) * (1 + ca) + sa
    x = x + ga * _A_ref(h, A_k_cache, A_v_cache, A_wq, A_wo)
    h = _layernorm(x, axis=-1) * (1 + cb) + sb
    x = x + gb * _B_ref(h, B_w1, B_w2)
    return x
```

```cpp
#include <cuda_runtime.h>
#include <cuda_bf16.h>
#include <cuda.h>
#include <stdint.h>

namespace {

constexpr int NHELP = 4;
constexpr int NTHREADS = 384;

constexpr uint32_t SM_STASH = 0;
constexpr uint32_t SM_RING = 98304;
constexpr uint32_t SM_MISC = 229376;
constexpr uint32_t SM_TOTAL = 232448;
constexpr uint32_t MB_FULL = SM_MISC + 0;
constexpr uint32_t MB_EMPTY = SM_MISC + 32;
constexpr uint32_t MB_XFULL = SM_MISC + 64;
constexpr uint32_t MB_MOD = SM_MISC + 88;
constexpr uint32_t MB_A2 = SM_MISC + 96;
constexpr uint32_t MB_PST = SM_MISC + 128;
constexpr uint32_t MB_SLOT0 = SM_MISC + 192;
constexpr uint32_t SM_RED = SM_MISC + 256;
constexpr uint32_t SM_MODBUF = SM_MISC + 512;

__device__ uint4 g_part[16 * 8 * 4 * 8 * 8 * 32];
__device__ __align__(1024) __nv_bfloat16 g_a2[2048 * 512];
__device__ __align__(1024) __nv_bfloat16 g_x1[2048 * 512];
__device__ __align__(128) uint2 g_modll[512];
__device__ __align__(128) uint4 g_st1[2048];
__device__ __align__(128) float4 g_st2[2048 * 2];
__device__ __align__(128) __nv_bfloat16 g_vec[3 * 512];
__device__ __align__(128) float4 g_uv[896];
__device__ __align__(128) unsigned g_cnt[17 * 32];
__device__ __align__(128) unsigned g_epoch[132 * 8];
#define TS(role, i) do {} while (0)
#define TSC(i) do {} while (0)

constexpr uint32_t SPIN_LIMIT = 1u << 22;

__device__ __forceinline__ long long globaltimer() { long long t; asm volatile("mov.u64 %0, %%clock64;" : "=l"(t)); return t; }
__device__ __forceinline__ void mbar_init(uint32_t bar, uint32_t cnt) {
  asm volatile("mbarrier.init.shared::cta.b64 [%0], %1;" ::"r"(bar), "r"(cnt) : "memory");
}
__device__ __forceinline__ void mbar_expect_tx(uint32_t bar, uint32_t bytes) {
  asm volatile("mbarrier.arrive.expect_tx.shared::cta.b64 _, [%0], %1;" ::"r"(bar), "r"(bytes) : "memory");
}
__device__ __forceinline__ void mbar_arrive(uint32_t bar) {
  asm volatile("mbarrier.arrive.shared::cta.b64 _, [%0];" ::"r"(bar) : "memory");
}
__device__ __forceinline__ void mbar_arrive_pred(uint32_t bar, uint32_t lane) {
  asm volatile("{\n.reg .pred p;\nsetp.eq.u32 p, %1, 0;\n@p mbarrier.arrive.shared::cta.b64 _, [%0];\n}" ::"r"(bar), "r"(lane) : "memory");
}
__device__ __forceinline__ void mbar_wait(uint32_t bar, uint32_t parity) {
  asm volatile(
      "{\n.reg .pred p;\n.reg .u32 c;\n"
      "mbarrier.try_wait.parity.shared::cta.b64 p, [%0], %1;\n"
      "@p bra DONE;\n"
      "mov.u32 c, 0;\n"
      "LOOP:\n"
      "mbarrier.try_wait.parity.shared::cta.b64 p, [%0], %1;\n"
      "@p bra DONE;\n"
      "add.u32 c, c, 1;\n"
      "setp.lt.u32 p, c, %2;\n"
      "@p bra LOOP;\n"
      "trap;\n"
      "DONE:\n}" ::"r"(bar), "r"(parity), "n"(SPIN_LIMIT) : "memory");
}
__device__ __forceinline__ void bar_sync(uint32_t id, uint32_t n) { asm volatile("bar.sync %0, %1;" ::"r"(id), "r"(n) : "memory"); }
__device__ __forceinline__ void bar_arrive(uint32_t id, uint32_t n) { asm volatile("bar.arrive %0, %1;" ::"r"(id), "r"(n) : "memory"); }
__device__ __forceinline__ void tma3d(uint32_t dst, const CUtensorMap* m, uint32_t bar, int c0, int c1, int c2) {
  asm volatile("cp.async.bulk.tensor.3d.shared::cluster.global.mbarrier::complete_tx::bytes [%0], [%1, {%3, %4, %5}], [%2];"
               ::"r"(dst), "l"(m), "r"(bar), "r"(c0), "r"(c1), "r"(c2) : "memory");
}
__device__ __forceinline__ void tma2d(uint32_t dst, const CUtensorMap* m, uint32_t bar, int c0, int c1) {
  asm volatile("cp.async.bulk.tensor.2d.shared::cluster.global.mbarrier::complete_tx::bytes [%0], [%1, {%3, %4}], [%2];"
               ::"r"(dst), "l"(m), "r"(bar), "r"(c0), "r"(c1) : "memory");
}
__device__ __forceinline__ void prefetch_tmap(const CUtensorMap* m) {
  asm volatile("prefetch.tensormap [%0];" ::"l"(m) : "memory");
}
__device__ __forceinline__ void wg_fence() { asm volatile("wgmma.fence.sync.aligned;" ::: "memory"); }
__device__ __forceinline__ void wg_commit() { asm volatile("wgmma.commit_group.sync.aligned;" ::: "memory"); }
template <int N> __device__ __forceinline__ void wg_wait() { asm volatile("wgmma.wait_group.sync.aligned %0;" ::"n"(N) : "memory"); }
template <int N> __device__ __forceinline__ void pin(float (&d)[N]) {
#pragma unroll
  for (int i = 0; i < N; i++) asm volatile("" : "+f"(d[i])::"memory");
}
template <int N> __device__ __forceinline__ void pin(uint32_t (&d)[N]) {
#pragma unroll
  for (int i = 0; i < N; i++) asm volatile("" : "+r"(d[i])::"memory");
}
__device__ __forceinline__ uint64_t mkdesc(uint32_t addr, uint32_t lbo) {
  uint32_t lo = (addr >> 4) | ((lbo >> 4) << 16);
  return ((uint64_t)0x40000040u << 32) | lo;
}
__device__ __forceinline__ uint32_t pack2(float lo, float hi) {
  uint32_t r;
  asm("cvt.rn.bf16x2.f32 %0, %1, %2;" : "=r"(r) : "f"(hi), "f"(lo));
  return r;
}
__device__ __forceinline__ float bf_lo(uint32_t w) { return __uint_as_float(w << 16); }
__device__ __forceinline__ float bf_hi(uint32_t w) { return __uint_as_float(w & 0xffff0000u); }
__device__ __forceinline__ float bf_round(float x) { return __bfloat162float(__float2bfloat16_rn(x)); }
__device__ __forceinline__ uint32_t bf2_fma(uint32_t a, uint32_t b, uint32_t c) {
  uint32_t r; asm("fma.rn.bf16x2 %0, %1, %2, %3;" : "=r"(r) : "r"(a), "r"(b), "r"(c)); return r;
}
__device__ __forceinline__ uint32_t bf2_mul(uint32_t a, uint32_t b) {
  uint32_t r; asm("mul.rn.bf16x2 %0, %1, %2;" : "=r"(r) : "r"(a), "r"(b)); return r;
}
__device__ __forceinline__ uint32_t bf2_add(uint32_t a, uint32_t b) {
  uint32_t r; asm("add.rn.bf16x2 %0, %1, %2;" : "=r"(r) : "r"(a), "r"(b)); return r;
}
__device__ __forceinline__ float ex2(float x) { float r; asm("ex2.approx.ftz.f32 %0, %1;" : "=f"(r) : "f"(x)); return r; }
__device__ __forceinline__ float tanh_hw(float x) { float r; asm("tanh.approx.f32 %0, %1;" : "=f"(r) : "f"(x)); return r; }
__device__ __forceinline__ void sts128(uint32_t a, uint32_t x, uint32_t y, uint32_t z, uint32_t w) {
  asm volatile("st.shared.v4.b32 [%0], {%1, %2, %3, %4};" ::"r"(a), "r"(x), "r"(y), "r"(z), "r"(w) : "memory");
}
__device__ __forceinline__ void lds128(uint32_t a, uint32_t& x, uint32_t& y, uint32_t& z, uint32_t& w) {
  asm volatile("ld.shared.v4.b32 {%0, %1, %2, %3}, [%4];" : "=r"(x), "=r"(y), "=r"(z), "=r"(w) : "r"(a) : "memory");
}
__device__ __forceinline__ void ldsm4(uint32_t a, uint32_t& x, uint32_t& y, uint32_t& z, uint32_t& w) {
  asm volatile("ldmatrix.sync.aligned.m8n8.x4.shared.b16 {%0, %1, %2, %3}, [%4];" : "=r"(x), "=r"(y), "=r"(z), "=r"(w) : "r"(a) : "memory");
}
__device__ __forceinline__ uint4 ldg_nc(const void* p) {
  uint4 v; asm volatile("ld.global.nc.L1::no_allocate.v4.b32 {%0, %1, %2, %3}, [%4];" : "=r"(v.x), "=r"(v.y), "=r"(v.z), "=r"(v.w) : "l"(p)); return v;
}
__device__ __forceinline__ uint4 ldg_cg(const void* p) {
  uint4 v; asm volatile("ld.global.cg.v4.b32 {%0, %1, %2, %3}, [%4];" : "=r"(v.x), "=r"(v.y), "=r"(v.z), "=r"(v.w) : "l"(p) : "memory"); return v;
}
__device__ __forceinline__ uint4 ldg_ll(const void* p) {
  unsigned long long a, b;
  asm volatile("ld.relaxed.gpu.global.v2.b64 {%0, %1}, [%2];" : "=l"(a), "=l"(b) : "l"(p) : "memory");
  return make_uint4((uint32_t)a, (uint32_t)(a >> 32), (uint32_t)b, (uint32_t)(b >> 32));
}
__device__ __forceinline__ void stg_ll(void* p, uint32_t v, uint32_t tag) {
  unsigned long long a = ((unsigned long long)tag << 32) | v;
  asm volatile("st.relaxed.gpu.global.b64 [%0], %1;" ::"l"(p), "l"(a) : "memory");
}
__device__ __forceinline__ void stg128(void* p, uint32_t x, uint32_t y, uint32_t z, uint32_t w) {
  asm volatile("st.global.v4.b32 [%0], {%1, %2, %3, %4};" ::"l"(p), "r"(x), "r"(y), "r"(z), "r"(w) : "memory");
}
__device__ __forceinline__ void cp_async16(uint32_t dst, const void* src) {
  asm volatile("cp.async.cg.shared.global [%0], [%1], 16;" ::"r"(dst), "l"(src) : "memory");
}
__device__ __forceinline__ void cp_commit() { asm volatile("cp.async.commit_group;" ::: "memory"); }
template <int N> __device__ __forceinline__ void cp_wait() { asm volatile("cp.async.wait_group %0;" ::"n"(N) : "memory"); }
__device__ __forceinline__ void signal_cnt(unsigned* p) {
  asm volatile("fence.acq_rel.gpu;\nred.relaxed.gpu.global.add.u32 [%0], 1;" ::"l"(p) : "memory");
}
__device__ __forceinline__ void wait_cnt(const unsigned* p, unsigned target) {
  unsigned v, it = 0;
  while (true) {
    asm volatile("ld.acquire.gpu.global.u32 %0, [%1];" : "=r"(v) : "l"(p) : "memory");
    if ((int)(v - target) >= 0) break;
    if (++it > SPIN_LIMIT) __trap();
  }
}

#define ACC8(d, i) "+f"(d[i]), "+f"(d[i+1]), "+f"(d[i+2]), "+f"(d[i+3]), "+f"(d[i+4]), "+f"(d[i+5]), "+f"(d[i+6]), "+f"(d[i+7])
__device__ __forceinline__ void wgmma_rs128_k(float (&d)[64], uint32_t a0, uint32_t a1, uint32_t a2, uint32_t a3, uint64_t db, int scale_d) {
  asm volatile("{\n.reg .pred p;\nsetp.ne.b32 p, %69, 0;\n"
    "wgmma.mma_async.sync.aligned.m64n128k16.f32.bf16.bf16 {"
    "%0, %1, %2, %3, %4, %5, %6, %7, %8, %9, %10, %11, %12, %13, %14, %15, "
    "%16, %17, %18, %19, %20, %21, %22, %23, %24, %25, %26, %27, %28, %29, %30, %31, "
    "%32, %33, %34, %35, %36, %37, %38, %39, %40, %41, %42, %43, %44, %45, %46, %47, "
    "%48, %49, %50, %51, %52, %53, %54, %55, %56, %57, %58, %59, %60, %61, %62, %63}, "
    "{%64, %65, %66, %67}, %68, p, 1, 1, 0;\n}"
    : ACC8(d, 0), ACC8(d, 8), ACC8(d, 16), ACC8(d, 24), ACC8(d, 32), ACC8(d, 40), ACC8(d, 48), ACC8(d, 56)
    : "r"(a0), "r"(a1), "r"(a2), "r"(a3), "l"(db), "r"(scale_d));
}

__device__ __forceinline__ void wgmma_rs128_mn(float (&d)[64], uint32_t a0, uint32_t a1, uint32_t a2, uint32_t a3, uint64_t db, int scale_d) {
  asm volatile("{\n.reg .pred p;\nsetp.ne.b32 p, %69, 0;\n"
    "wgmma.mma_async.sync.aligned.m64n128k16.f32.bf16.bf16 {"
    "%0, %1, %2, %3, %4, %5, %6, %7, %8, %9, %10, %11, %12, %13, %14, %15, "
    "%16, %17, %18, %19, %20, %21, %22, %23, %24, %25, %26, %27, %28, %29, %30, %31, "
    "%32, %33, %34, %35, %36, %37, %38, %39, %40, %41, %42, %43, %44, %45, %46, %47, "
    "%48, %49, %50, %51, %52, %53, %54, %55, %56, %57, %58, %59, %60, %61, %62, %63}, "
    "{%64, %65, %66, %67}, %68, p, 1, 1, 1;\n}"
    : ACC8(d, 0), ACC8(d, 8), ACC8(d, 16), ACC8(d, 24), ACC8(d, 32), ACC8(d, 40), ACC8(d, 48), ACC8(d, 56)
    : "r"(a0), "r"(a1), "r"(a2), "r"(a3), "l"(db), "r"(scale_d));
}

__device__ __forceinline__ void wgmma_ss224_mn(float (&d)[112], uint64_t da, uint64_t db, int scale_d) {
  asm volatile("{\n.reg .pred p;\nsetp.ne.b32 p, %114, 0;\n"
    "wgmma.mma_async.sync.aligned.m64n224k16.f32.bf16.bf16 {"
    "%0, %1, %2, %3, %4, %5, %6, %7, %8, %9, %10, %11, %12, %13, %14, %15, "
    "%16, %17, %18, %19, %20, %21, %22, %23, %24, %25, %26, %27, %28, %29, %30, %31, "
    "%32, %33, %34, %35, %36, %37, %38, %39, %40, %41, %42, %43, %44, %45, %46, %47, "
    "%48, %49, %50, %51, %52, %53, %54, %55, %56, %57, %58, %59, %60, %61, %62, %63, "
    "%64, %65, %66, %67, %68, %69, %70, %71, %72, %73, %74, %75, %76, %77, %78, %79, "
    "%80, %81, %82, %83, %84, %85, %86, %87, %88, %89, %90, %91, %92, %93, %94, %95, "
    "%96, %97, %98, %99, %100, %101, %102, %103, %104, %105, %106, %107, %108, %109, %110, %111}, "
    "%112, %113, p, 1, 1, 0, 1;\n}"
    : ACC8(d, 0), ACC8(d, 8), ACC8(d, 16), ACC8(d, 24), ACC8(d, 32), ACC8(d, 40), ACC8(d, 48), ACC8(d, 56), ACC8(d, 64), ACC8(d, 72), ACC8(d, 80), ACC8(d, 88), ACC8(d, 96), ACC8(d, 104)
    : "l"(da), "l"(db), "r"(scale_d));
}

constexpr uint32_t SB = 1024;

struct Params {
  const __nv_bfloat16* x;
  const __nv_bfloat16* c;
  const __nv_bfloat16* wmod;
  const __nv_bfloat16* w1;
  __nv_bfloat16* out;
};

template <int NK, int AOFF, int NA>
__device__ __forceinline__ void tile_rs_mn(float (&acc)[64], const uint32_t (&A)[NA], uint32_t addr, uint32_t lbo, int first_scale) {
#pragma unroll
  for (int ks = 0; ks < NK; ks++)
    wgmma_rs128_mn(acc, A[AOFF + 4 * ks], A[AOFF + 4 * ks + 1], A[AOFF + 4 * ks + 2], A[AOFF + 4 * ks + 3],
                   mkdesc(addr + ks * 2048, lbo), ks == 0 ? first_scale : 1);
}
__device__ __forceinline__ void tile_qk(float (&S)[64], const uint32_t (&Q)[32], uint32_t addr) {
#pragma unroll
  for (int ks = 0; ks < 8; ks++)
    wgmma_rs128_k(S, Q[4 * ks], Q[4 * ks + 1], Q[4 * ks + 2], Q[4 * ks + 3],
                  mkdesc(addr + (ks >> 2) * 16384 + (ks & 3) * 32, 16), ks == 0 ? 0 : 1);
}

template <int QQ>
__device__ __forceinline__ void ln_quarter(uint32_t (&A)[128], uint32_t xaddr, uint32_t maddr, float r0, float n0, float r1, float n1) {
#pragma unroll
  for (int s = 0; s < 8; s++)
    ldsm4((xaddr + (s >> 2) * 8192) ^ ((s & 3) << 5), A[QQ * 32 + 4 * s], A[QQ * 32 + 4 * s + 1], A[QQ * 32 + 4 * s + 2], A[QQ * 32 + 4 * s + 3]);
#pragma unroll
  for (int s = 0; s < 8; s++) {
    uint32_t cl, ch, sl, sh;
    lds128(maddr + (QQ * 8 + s) * 64, cl, ch, sl, sh);
    uint32_t* a = &A[QQ * 32 + 4 * s];
    a[0] = bf2_fma(pack2(fmaf(bf_lo(a[0]), r0, n0), fmaf(bf_hi(a[0]), r0, n0)), cl, sl);
    a[1] = bf2_fma(pack2(fmaf(bf_lo(a[1]), r1, n1), fmaf(bf_hi(a[1]), r1, n1)), cl, sl);
    a[2] = bf2_fma(pack2(fmaf(bf_lo(a[2]), r0, n0), fmaf(bf_hi(a[2]), r0, n0)), ch, sh);
    a[3] = bf2_fma(pack2(fmaf(bf_lo(a[3]), r1, n1), fmaf(bf_hi(a[3]), r1, n1)), ch, sh);
  }
}

__device__ __forceinline__ void softmax_step(float (&S)[64], float& m0, float& m1, float& l0, float& l1, float& al0, float& al1) {
  constexpr float SC = 0.08838834764831845f * 1.4426950408889634f;
  float a0 = fmaxf(S[0], S[1]), a1 = fmaxf(S[2], S[3]), b0 = fmaxf(S[4], S[5]), b1 = fmaxf(S[6], S[7]);
#pragma unroll
  for (int j = 8; j < 64; j += 8) {
    a0 = fmaxf(a0, fmaxf(S[j], S[j + 1]));
    a1 = fmaxf(a1, fmaxf(S[j + 2], S[j + 3]));
    b0 = fmaxf(b0, fmaxf(S[j + 4], S[j + 5]));
    b1 = fmaxf(b1, fmaxf(S[j + 6], S[j + 7]));
  }
  a0 = fmaxf(a0, b0);
  a1 = fmaxf(a1, b1);
  a0 = fmaxf(a0, __shfl_xor_sync(0xffffffffu, a0, 1));
  a1 = fmaxf(a1, __shfl_xor_sync(0xffffffffu, a1, 1));
  a0 = fmaxf(a0, __shfl_xor_sync(0xffffffffu, a0, 2));
  a1 = fmaxf(a1, __shfl_xor_sync(0xffffffffu, a1, 2));
  a0 = fmaxf(a0, m0);
  a1 = fmaxf(a1, m1);
  al0 = ex2((m0 - a0) * SC);
  al1 = ex2((m1 - a1) * SC);
  m0 = a0;
  m1 = a1;
  const float nb0 = -a0 * SC, nb1 = -a1 * SC;
  float s0 = 0.f, s1 = 0.f, t0 = 0.f, t1 = 0.f;
#pragma unroll
  for (int j = 0; j < 64; j += 4) {
    S[j] = ex2(fmaf(S[j], SC, nb0));
    S[j + 1] = ex2(fmaf(S[j + 1], SC, nb0));
    S[j + 2] = ex2(fmaf(S[j + 2], SC, nb1));
    S[j + 3] = ex2(fmaf(S[j + 3], SC, nb1));
    s0 += S[j];
    t0 += S[j + 1];
    s1 += S[j + 2];
    t1 += S[j + 3];
  }
  l0 = fmaf(l0, al0, s0 + t0);
  l1 = fmaf(l1, al1, s1 + t1);
}

__device__ __forceinline__ float quad_sum(float v) {
  v += __shfl_xor_sync(0xffffffffu, v, 1);
  v += __shfl_xor_sync(0xffffffffu, v, 2);
  return v;
}

template <int S0>
__device__ __forceinline__ void silu_half(const float (&Z)[112], uint32_t (&H)[56], uint32_t uvaddr, float hr0, float nm0, float hr1, float nm1) {
#pragma unroll
  for (int s = S0; s < S0 + 7; s++) {
#pragma unroll
    for (int hf = 0; hf < 2; hf++) {
      uint32_t u0, u1, v0, v1;
      lds128(uvaddr + (2 * s + hf) * 64, u0, u1, v0, v1);
      const float* z = &Z[8 * s + 4 * hf];
      float a = fmaf(z[0], hr0, fmaf(__uint_as_float(u0), nm0, __uint_as_float(v0)));
      float b = fmaf(z[1], hr0, fmaf(__uint_as_float(u1), nm0, __uint_as_float(v1)));
      float c = fmaf(z[2], hr1, fmaf(__uint_as_float(u0), nm1, __uint_as_float(v0)));
      float d = fmaf(z[3], hr1, fmaf(__uint_as_float(u1), nm1, __uint_as_float(v1)));
      H[4 * s + 2 * hf] = pack2(fmaf(a, tanh_hw(a), a), fmaf(b, tanh_hw(b), b));
      H[4 * s + 2 * hf + 1] = pack2(fmaf(c, tanh_hw(c), c), fmaf(d, tanh_hw(d), d));
    }
  }
}

__device__ __forceinline__ void store_partial(const float (&acc)[64], uint4* dst) {
#pragma unroll
  for (int i = 0; i < 8; i++)
    stg128(dst + i * 32, pack2(acc[8 * i], acc[8 * i + 1]), pack2(acc[8 * i + 2], acc[8 * i + 3]),
           pack2(acc[8 * i + 4], acc[8 * i + 5]), pack2(acc[8 * i + 6], acc[8 * i + 7]));
}

__device__ __forceinline__ void ln_scalars(float mean, float var, float& rstd, float& mb) {
  mb = bf_round(mean);
  rstd = 1.0f / bf_round(sqrtf(bf_round(bf_round(var) + 1e-5f)));
}

#define TURN_BEGIN() bar_sync(1 + wg, 256)
#define TURN_END() bar_arrive(2 - wg, 256)
#define FULLB(s) (SB + MB_FULL + 8 * (s))
#define EMPTYB(s) (SB + MB_EMPTY + 8 * (s))
#define STAGE(s) (SB + SM_RING + 32768 * (s))

__device__ __forceinline__ void consumer(const Params& p, const int mb) {
  const int tid = threadIdx.x;
  const int wg = __shfl_sync(0xffffffffu, tid >> 7, 0);
  const int warp = tid >> 5, lane = tid & 31, q = lane & 3;
  const int t = mb >> 3, g = mb & 7;
  TSC(0);
  uint32_t tag;
  {
    const uint4 w0 = ldg_nc(p.wmod + (size_t)tid * 3072 + mb * 8);
    const uint4 w1 = ldg_nc(p.wmod + (size_t)(tid + 256) * 3072 + mb * 8);
    const float c0 = __bfloat162float(p.c[tid]), c1 = __bfloat162float(p.c[tid + 256]);
    const int row = t * 128 + g * 16 + warp * 2;
    uint4 xv[4];
#pragma unroll
    for (int i = 0; i < 4; i++) xv[i] = ldg_nc(p.x + (size_t)row * 512 + i * 256 + lane * 8);
    asm volatile("ld.relaxed.gpu.global.u32 %0, [%1];" : "=r"(tag) : "l"(&g_epoch[blockIdx.x * 8]) : "memory");
    tag += 1;
    bar_sync(0, NTHREADS);
    if (wg == 1) bar_arrive(1, 256);

    const float s0 = bf_round(c0 / (1.0f + __expf(-c0))), s1 = bf_round(c1 / (1.0f + __expf(-c1)));
    float a[8];
    a[0] = fmaf(s0, bf_lo(w0.x), s1 * bf_lo(w1.x)); a[1] = fmaf(s0, bf_hi(w0.x), s1 * bf_hi(w1.x));
    a[2] = fmaf(s0, bf_lo(w0.y), s1 * bf_lo(w1.y)); a[3] = fmaf(s0, bf_hi(w0.y), s1 * bf_hi(w1.y));
    a[4] = fmaf(s0, bf_lo(w0.z), s1 * bf_lo(w1.z)); a[5] = fmaf(s0, bf_hi(w0.z), s1 * bf_hi(w1.z));
    a[6] = fmaf(s0, bf_lo(w0.w), s1 * bf_lo(w1.w)); a[7] = fmaf(s0, bf_hi(w0.w), s1 * bf_hi(w1.w));
    {
      const bool u = lane & 16;
#pragma unroll
      for (int i = 0; i < 4; i++) {
        float snd = u ? a[i] : a[i + 4], kp = u ? a[i + 4] : a[i];
        a[i] = kp + __shfl_xor_sync(0xffffffffu, snd, 16);
      }
      const bool v = lane & 8;
#pragma unroll
      for (int i = 0; i < 2; i++) {
        float snd = v ? a[i] : a[i + 2], kp = v ? a[i + 2] : a[i];
        a[i] = kp + __shfl_xor_sync(0xffffffffu, snd, 8);
      }
      const bool w = lane & 4;
      float snd = w ? a[0] : a[1], kp = w ? a[1] : a[0];
      a[0] = quad_sum(kp + __shfl_xor_sync(0xffffffffu, snd, 4));
      if (q == 0) asm volatile("st.shared.f32 [%0], %1;" ::"r"(SB + SM_RED + warp * 32 + (lane >> 2) * 4), "f"(a[0]) : "memory");
    }
    if (warp != 0) {
      bar_arrive(3, 256);
    } else {
      bar_sync(3, 256);
      float v = 0.f;
#pragma unroll
      for (int w = 0; w < 8; w++) {
        float f;
        asm volatile("ld.shared.f32 %0, [%1];" : "=f"(f) : "r"(SB + SM_RED + w * 32 + (lane & 7) * 4) : "memory");
        v += f;
      }
      v = bf_round(v);
      if (mb >= 64) v = 1.0f + v;
      const float vn = __shfl_down_sync(0xffffffffu, v, 1);
      if (lane < 8 && !(lane & 1)) stg_ll(&g_modll[mb * 4 + (lane >> 1)], pack2(v, vn), tag);
    }
    float f[2][16];
#pragma unroll
    for (int i = 0; i < 4; i++) {
      float* d = &f[i >> 1][(i & 1) * 8];
      d[0] = bf_lo(xv[i].x); d[1] = bf_hi(xv[i].x); d[2] = bf_lo(xv[i].y); d[3] = bf_hi(xv[i].y);
      d[4] = bf_lo(xv[i].z); d[5] = bf_hi(xv[i].z); d[6] = bf_lo(xv[i].w); d[7] = bf_hi(xv[i].w);
    }
    float m[2] = {0.f, 0.f}, vr[2] = {0.f, 0.f};
#pragma unroll
    for (int i = 0; i < 16; i++) { m[0] += f[0][i]; m[1] += f[1][i]; }
#pragma unroll
    for (int o = 16; o; o >>= 1) { m[0] += __shfl_xor_sync(0xffffffffu, m[0], o); m[1] += __shfl_xor_sync(0xffffffffu, m[1], o); }
    m[0] *= (1.0f / 512); m[1] *= (1.0f / 512);
#pragma unroll
    for (int i = 0; i < 16; i++) {
      float d0 = f[0][i] - m[0], d1 = f[1][i] - m[1];
      vr[0] = fmaf(d0, d0, vr[0]); vr[1] = fmaf(d1, d1, vr[1]);
    }
#pragma unroll
    for (int o = 16; o; o >>= 1) { vr[0] += __shfl_xor_sync(0xffffffffu, vr[0], o); vr[1] += __shfl_xor_sync(0xffffffffu, vr[1], o); }
    float rstd, mbf;
    ln_scalars((lane & 2) ? m[1] : m[0], ((lane & 2) ? vr[1] : vr[0]) * (1.0f / 512), rstd, mbf);
    if (lane < 4) stg_ll((uint2*)&g_st1[row] + lane, __float_as_uint((lane & 1) ? -mbf * rstd : rstd), tag);
  }
  TSC(1);
  const int row0 = t * 128 + warp * 16 + (lane >> 2);
  float acc[64];
  uint32_t Q[32];
  const uint32_t stash = SB + SM_STASH + wg * 49152 + (tid & 127) * 16;
  {
    float r0, n0, r1, n1;
    {
      uint4 sa, sb2;
      uint32_t it = 0;
      while (true) {
        sa = ldg_ll(&g_st1[row0]);
        sb2 = ldg_ll(&g_st1[row0 + 8]);
        if (sa.y == tag && sa.w == tag && sb2.y == tag && sb2.w == tag) break;
        if (++it > SPIN_LIMIT) __trap();
      }
      r0 = __uint_as_float(sa.x); n0 = __uint_as_float(sa.z);
      r1 = __uint_as_float(sb2.x); n1 = __uint_as_float(sb2.z);
      __syncwarp();
    }
    TSC(2);
    uint32_t A[128];
    const uint32_t xrow = ((warp & 3) * 16 + (lane & 15)) * 128 + (((lane >> 4) ^ (lane & 7)) << 4);
    const uint32_t maddr = SB + SM_MODBUF + q * 16;
    mbar_wait(SB + MB_MOD, 0);
    TSC(3);
    mbar_wait(FULLB(0), 0);
    TSC(4);
    ln_quarter<0>(A, STAGE(0) + wg * 16384 + xrow, maddr, r0, n0, r1, n1);
    mbar_arrive_pred(EMPTYB(0), lane);
    const uint32_t xst = SB + SM_STASH + wg * 49152 + xrow;
#define QSTEP0(KT)                                                                   \
    TURN_BEGIN();                                                                    \
    mbar_wait(FULLB((1 + KT) & 3), KT == 3);                                         \
    pin(A);                                                                          \
    wg_fence();                                                                      \
    tile_rs_mn<8, KT * 32>(acc, A, STAGE((1 + KT) & 3), 16384, KT != 0);             \
    wg_commit();                                                                     \
    TURN_END();                                                                      \
    if (KT < 3) {                                                                    \
      mbar_wait(SB + MB_XFULL + 8 * (KT & 3), 0);                                    \
      ln_quarter<(KT + 1) & 3>(A, xst + KT * 16384, maddr, r0, n0, r1, n1);          \
    }                                                                                \
    wg_wait<0>();                                                                    \
    mbar_arrive_pred(EMPTYB((1 + KT) & 3), lane);
    QSTEP0(0) QSTEP0(1) QSTEP0(2) QSTEP0(3)
#undef QSTEP0
    TSC(5);
#pragma unroll 1
    for (int j = 0; j < 3; j++) {
      pin(acc);
#pragma unroll
      for (int i = 0; i < 8; i++)
        sts128(stash + j * 16384 + i * 2048, pack2(acc[8 * i], acc[8 * i + 1]), pack2(acc[8 * i + 2], acc[8 * i + 3]),
               pack2(acc[8 * i + 4], acc[8 * i + 5]), pack2(acc[8 * i + 6], acc[8 * i + 7]));
#define QSTEP(KT)                                                                    \
      TURN_BEGIN();                                                                  \
      mbar_wait(FULLB((1 + KT) & 3), (j + 1 + (KT == 3)) & 1);                       \
      wg_fence();                                                                    \
      tile_rs_mn<8, KT * 32>(acc, A, STAGE((1 + KT) & 3), 16384, KT != 0);           \
      wg_commit();                                                                   \
      TURN_END();                                                                    \
      wg_wait<0>();                                                                  \
      mbar_arrive_pred(EMPTYB((1 + KT) & 3), lane);
      QSTEP(0) QSTEP(1) QSTEP(2) QSTEP(3)
#undef QSTEP
    }
    pin(acc);
#pragma unroll
    for (int i = 0; i < 32; i++) Q[i] = pack2(acc[2 * i], acc[2 * i + 1]);
  }
  TSC(6);
  uint32_t A[128];
  {
    float S[64];
    uint32_t P[32];
    float m0 = -INFINITY, m1 = -INFINITY, l0 = 0.f, l1 = 0.f, al0, al1;
    TURN_BEGIN();
    mbar_wait(FULLB(1), 0);
    pin(Q);
    wg_fence();
    tile_qk(S, Q, STAGE(1));
    wg_commit();
    TURN_END();
    wg_wait<0>();
    pin(S);
    mbar_arrive_pred(EMPTYB(1), lane);
    softmax_step(S, m0, m1, l0, l1, al0, al1);
#pragma unroll
    for (int i = 0; i < 32; i++) P[i] = pack2(S[2 * i], S[2 * i + 1]);
#pragma unroll 1
    for (int j = 1; j < 16; j++) {
      const uint32_t st = (2 * j) & 3, par = (j >> 1) & 1;
      TURN_BEGIN();
      mbar_wait(FULLB(st), par);
      pin(Q); pin(P); pin(acc);
      wg_fence();
      tile_qk(S, Q, STAGE(st));
      wg_commit();
      mbar_wait(FULLB(st + 1), par);
      tile_rs_mn<8, 0>(acc, P, STAGE(st + 1), 16384, (j & 3) != 1);
      wg_commit();
      TURN_END();
      wg_wait<1>();
      pin(S);
      mbar_arrive_pred(EMPTYB(st), lane);
      const bool newhead = (j & 3) == 0;
      float i0 = 0.f, i1 = 0.f;
      if (newhead) {
        i0 = 1.0f / quad_sum(l0);
        i1 = 1.0f / quad_sum(l1);
        m0 = -INFINITY; m1 = -INFINITY;
      }
      if ((j & 3) == 3 && j != 15) {
#pragma unroll
        for (int i = 0; i < 8; i++) lds128(stash + (j >> 2) * 16384 + i * 2048, Q[4 * i], Q[4 * i + 1], Q[4 * i + 2], Q[4 * i + 3]);
      }
      softmax_step(S, m0, m1, l0, l1, al0, al1);
      if (newhead) { al0 = i0; al1 = i1; }
      wg_wait<0>();
      pin(acc);
      mbar_arrive_pred(EMPTYB(st + 1), lane);
#pragma unroll
      for (int i = 0; i < 32; i++) P[i] = pack2(S[2 * i], S[2 * i + 1]);
#pragma unroll
      for (int i = 0; i < 64; i += 4) { acc[i] *= al0; acc[i + 1] *= al0; acc[i + 2] *= al1; acc[i + 3] *= al1; }
      if (newhead) {
#pragma unroll
        for (int i = 0; i < 8; i++)
          sts128(stash + ((j >> 2) - 1) * 16384 + i * 2048, pack2(acc[8 * i], acc[8 * i + 1]), pack2(acc[8 * i + 2], acc[8 * i + 3]),
                 pack2(acc[8 * i + 4], acc[8 * i + 5]), pack2(acc[8 * i + 6], acc[8 * i + 7]));
      }
    }
    TURN_BEGIN();
    mbar_wait(FULLB(0), 0);
    pin(P); pin(acc);
    wg_fence();
    tile_rs_mn<8, 0>(acc, P, STAGE(0), 16384, 1);
    wg_commit();
    TURN_END();
#pragma unroll
    for (int i = 0; i < 24; i++) lds128(stash + i * 2048, A[4 * i], A[4 * i + 1], A[4 * i + 2], A[4 * i + 3]);
    const float i0 = 1.0f / quad_sum(l0), i1 = 1.0f / quad_sum(l1);
    wg_wait<0>();
    pin(acc);
    mbar_arrive_pred(EMPTYB(0), lane);
#pragma unroll
    for (int i = 0; i < 16; i++) {
      A[96 + 2 * i] = pack2(acc[4 * i] * i0, acc[4 * i + 1] * i0);
      A[96 + 2 * i + 1] = pack2(acc[4 * i + 2] * i1, acc[4 * i + 3] * i1);
    }
  }
  TSC(7);
  uint4* const part = g_part + ((size_t)(t * 8 + warp) * 4 * 8 + g) * 256 + lane;
  pin(A);
#pragma unroll 1
  for (int c = 0; c < 4; c++) {
#define OSTEP(KT)                                                                    \
    TURN_BEGIN();                                                                    \
    mbar_wait(FULLB((1 + KT) & 3), (c + (KT == 3)) & 1);                             \
    wg_fence();                                                                      \
    tile_rs_mn<8, KT * 32>(acc, A, STAGE((1 + KT) & 3), 16384, KT != 0);             \
    wg_commit();                                                                     \
    TURN_END();                                                                      \
    wg_wait<0>();                                                                    \
    mbar_arrive_pred(EMPTYB((1 + KT) & 3), lane);
    OSTEP(0) OSTEP(1) OSTEP(2) OSTEP(3)
#undef OSTEP
    pin(acc);
    store_partial(acc, part + c * 2048);
    __syncwarp();
    mbar_arrive_pred(SB + MB_PST + 8 * c, lane);
    TSC(8 + c);
  }
  uint32_t H[56];
  {
    float Z[112];
#pragma unroll
    for (int kt = 0; kt < 8; kt++) {
      if (!(kt & 1)) mbar_wait(SB + MB_A2 + 8 * (kt >> 1), 0);
      if (kt == 6) TSC(12);
      TURN_BEGIN();
      mbar_wait(FULLB((1 + kt) & 3), ((1 + kt) >> 2) & 1);
      wg_fence();
      const uint32_t aaddr = SB + SM_STASH + ((kt >> 1) % 3) * 32768 + (kt & 1) * 16384 + wg * 8192;
#pragma unroll
      for (int ks = 0; ks < 4; ks++)
        wgmma_ss224_mn(Z, mkdesc(aaddr + ks * 32, 16), mkdesc(STAGE((1 + kt) & 3) + ks * 2048, 8192), (kt | ks) != 0);
      wg_commit();
      TURN_END();
      if (kt < 7) {
        wg_wait<0>();
        mbar_arrive_pred(EMPTYB((1 + kt) & 3), lane);
        if (kt == 1) mbar_arrive_pred(SB + MB_SLOT0, lane);
      }
    }
    float hr0, nm0, hr1, nm1;
    {
      const uint4 a0 = ldg_cg(&g_st2[row0 * 2]), a1 = ldg_cg(&g_st2[row0 * 2 + 1]);
      const uint4 b0 = ldg_cg(&g_st2[row0 * 2 + 16]), b1 = ldg_cg(&g_st2[row0 * 2 + 17]);
      float d = (__uint_as_float(a0.x) + __uint_as_float(a1.x)) * (1.0f / 512);
      float v = fmaxf(fmaf(-d, d, (__uint_as_float(a0.y) + __uint_as_float(a1.y)) * (1.0f / 512)), 0.f);
      float rs, mbf;
      ln_scalars(__uint_as_float(a0.z) + d, v, rs, mbf);
      hr0 = 0.5f * rs; nm0 = -hr0 * mbf;
      d = (__uint_as_float(b0.x) + __uint_as_float(b1.x)) * (1.0f / 512);
      v = fmaxf(fmaf(-d, d, (__uint_as_float(b0.y) + __uint_as_float(b1.y)) * (1.0f / 512)), 0.f);
      ln_scalars(__uint_as_float(b0.z) + d, v, rs, mbf);
      hr1 = 0.5f * rs; nm1 = -hr1 * mbf;
    }
    wg_wait<0>();
    pin(Z);
    mbar_arrive_pred(EMPTYB(0), lane);
    TSC(13);
    const uint32_t uvaddr = SB + SM_MODBUF + q * 16;
    silu_half<0>(Z, H, uvaddr, hr0, nm0, hr1, nm1);
    TURN_BEGIN();
    mbar_wait(FULLB(1), 0);
    pin(H);
    wg_fence();
    tile_rs_mn<7, 0>(acc, H, STAGE(1), 14336, 0);
    wg_commit();
    TURN_END();
    wg_wait<0>();
    mbar_arrive_pred(EMPTYB(1), lane);
    silu_half<7>(Z, H, uvaddr, hr0, nm0, hr1, nm1);
  }
  TURN_BEGIN();
  mbar_wait(FULLB(2), 0);
  pin(H);
  wg_fence();
  tile_rs_mn<7, 28>(acc, H, STAGE(2), 14336, 1);
  wg_commit();
  TURN_END();
  wg_wait<0>();
  mbar_arrive_pred(EMPTYB(2), lane);
  pin(acc);
  store_partial(acc, part);
  __syncwarp();
  mbar_arrive_pred(SB + MB_PST + 8 * 4, lane);
  TSC(14);
#pragma unroll
  for (int c = 1; c < 4; c++) {
    TURN_BEGIN();
    mbar_wait(FULLB((1 + 2 * c) & 3), ((1 + 2 * c) >> 2) & 1);
    wg_fence();
    tile_rs_mn<7, 0>(acc, H, STAGE((1 + 2 * c) & 3), 14336, 0);
    wg_commit();
    TURN_END();
    wg_wait<0>();
    mbar_arrive_pred(EMPTYB((1 + 2 * c) & 3), lane);
    TURN_BEGIN();
    mbar_wait(FULLB((2 + 2 * c) & 3), ((2 + 2 * c) >> 2) & 1);
    wg_fence();
    tile_rs_mn<7, 28>(acc, H, STAGE((2 + 2 * c) & 3), 14336, 1);
    wg_commit();
    if (c < 3 || wg == 0) TURN_END();
    wg_wait<0>();
    mbar_arrive_pred(EMPTYB((2 + 2 * c) & 3), lane);
    pin(acc);
    store_partial(acc, part + c * 2048);
    __syncwarp();
    mbar_arrive_pred(SB + MB_PST + 8 * (4 + c), lane);
    TSC(14 + c);
  }
}

__device__ __forceinline__ uint32_t ring_acquire(int n, uint32_t bytes) {
  const int s = n & 3;
  mbar_wait(EMPTYB(s), ((n >> 2) & 1) ^ 1);
  mbar_expect_tx(FULLB(s), bytes);
  return s;
}
__device__ __forceinline__ void producer(const CUtensorMap* tmX, const CUtensorMap* tmWq, const CUtensorMap* tmK, const CUtensorMap* tmV,
                                         const CUtensorMap* tmWo, const CUtensorMap* tmW1, const CUtensorMap* tmW2, const int mb) {
  const int t = mb >> 3, g = mb & 7;
  mbar_expect_tx(FULLB(0), 32768);
  tma3d(STAGE(0), tmX, FULLB(0), 0, t * 128, 0);
  tma3d(STAGE(0) + 16384, tmX, FULLB(0), 0, t * 128 + 64, 0);
  int n = 1;
#pragma unroll 1
  for (int i = 0; i < 16; i++, n++) {
    const uint32_t s = ring_acquire(n, 32768);
    tma3d(STAGE(s), tmWq, FULLB(s), 0, (i & 3) * 128, (g * 4 + (((i >> 2) + 1) & 3)) * 2);
    if (i < 3) {
      const uint32_t xb = SB + MB_XFULL + 8 * i;
      mbar_expect_tx(xb, 32768);
      tma3d(SB + SM_STASH + i * 16384, tmX, xb, 0, t * 128, 2 * i + 2);
      tma3d(SB + SM_STASH + 49152 + i * 16384, tmX, xb, 0, t * 128 + 64, 2 * i + 2);
    }
  }
  const int kv0 = g * 2048 + 1536;
#pragma unroll 1
  for (int j = 0; j <= 16; j++) {
    if (j < 16) {
      const uint32_t s = ring_acquire(n++, 32768);
      tma3d(STAGE(s), tmK, FULLB(s), 0, kv0 + (j & 3) * 128, 0);
    }
    if (j > 0) {
      const uint32_t s = ring_acquire(n++, 32768);
      tma3d(STAGE(s), tmV, FULLB(s), 0, kv0 + ((j - 1) & 3) * 128, 0);
    }
  }
#pragma unroll 1
  for (int i = 0; i < 16; i++, n++) {
    const uint32_t s = ring_acquire(n, 32768);
    tma3d(STAGE(s), tmWo, FULLB(s), 0, (g * 4 + (i & 3)) * 128, (i >> 2) * 2);
  }
#pragma unroll 1
  for (int i = 0; i < 8; i++, n++) {
    const uint32_t s = ring_acquire(n, 32768);
#pragma unroll
    for (int pn = 0; pn < 4; pn++) tma2d(STAGE(s) + pn * 8192, tmW1, FULLB(s), g * 224 + pn * 64, i * 64);
  }
#pragma unroll 1
  for (int i = 0; i < 8; i++, n++) {
    const uint32_t s = ring_acquire(n, 28672);
    tma3d(STAGE(s), tmW2, FULLB(s), 0, g * 224 + (i & 1) * 112, (i >> 1) * 2);
  }
}

template <int I>
__device__ __forceinline__ void reduce_slot(uint32_t stg, int q, uint32_t (&o)[4]) {
  cp_wait<3 - I>();
  float s[8];
#pragma unroll
  for (int src = 0; src < 8; src++) {
    uint32_t w[4];
    lds128(stg + src * 4096 + I * 512, w[0], w[1], w[2], w[3]);
#pragma unroll
    for (int k = 0; k < 4; k++) {
      if (src == 0) { s[2 * k] = bf_lo(w[k]); s[2 * k + 1] = bf_hi(w[k]); }
      else { s[2 * k] += bf_lo(w[k]); s[2 * k + 1] += bf_hi(w[k]); }
    }
  }
  const uint32_t w0 = pack2(s[0], s[1]), w1 = pack2(s[2], s[3]), w2 = pack2(s[4], s[5]), w3 = pack2(s[6], s[7]);
  const bool b0 = q & 1, b1 = q & 2;
  const uint32_t r0 = __shfl_xor_sync(0xffffffffu, b0 ? w0 : w1, 1), r1 = __shfl_xor_sync(0xffffffffu, b0 ? w2 : w3, 1);
  const uint32_t alo = b0 ? r0 : w0, ahi = b0 ? w1 : r0, blo = b0 ? r1 : w2, bhi = b0 ? w3 : r1;
  const uint32_t e0 = __shfl_xor_sync(0xffffffffu, b1 ? alo : blo, 2), e1 = __shfl_xor_sync(0xffffffffu, b1 ? ahi : bhi, 2);
  o[0] = b1 ? e0 : alo; o[1] = b1 ? e1 : ahi; o[2] = b1 ? blo : e0; o[3] = b1 ? bhi : e1;
}

template <int I>
__device__ __forceinline__ void ex1_slot(const Params& p, uint32_t stg, int q, int off, int col, float piv, float& s1, float& s2) {
  const uint4 xv = ldg_nc(p.x + off + I * 16);
  const uint4 ga = ldg_cg(g_vec + col + I * 16);
  const uint4 cb = ldg_cg(g_vec + 512 + col + I * 16);
  uint32_t o[4];
  reduce_slot<I>(stg, q, o);
  o[0] = bf2_add(xv.x, bf2_mul(ga.x, o[0])); o[1] = bf2_add(xv.y, bf2_mul(ga.y, o[1]));
  o[2] = bf2_add(xv.z, bf2_mul(ga.z, o[2])); o[3] = bf2_add(xv.w, bf2_mul(ga.w, o[3]));
  stg128(g_a2 + off + I * 16, bf2_mul(o[0], cb.x), bf2_mul(o[1], cb.y), bf2_mul(o[2], cb.z), bf2_mul(o[3], cb.w));
  stg128(g_x1 + off + I * 16, o[0], o[1], o[2], o[3]);
#pragma unroll
  for (int k = 0; k < 4; k++) {
    const float a = bf_lo(o[k]) - piv, b = bf_hi(o[k]) - piv;
    s1 += a + b;
    s2 = fmaf(a, a, fmaf(b, b, s2));
  }
}
template <int I>
__device__ __forceinline__ void ex2_slot(const Params& p, uint32_t stg, int q, int off, int col) {
  const uint4 xv = ldg_cg(g_x1 + off + I * 16);
  const uint4 gb = ldg_cg(g_vec + 1024 + col + I * 16);
  uint32_t o[4];
  reduce_slot<I>(stg, q, o);
  stg128(p.out + off + I * 16, bf2_add(xv.x, bf2_mul(gb.x, o[0])), bf2_add(xv.y, bf2_mul(gb.y, o[1])),
         bf2_add(xv.z, bf2_mul(gb.z, o[2])), bf2_add(xv.w, bf2_mul(gb.w, o[3])));
}

__device__ __forceinline__ void reducer(const Params& p, const CUtensorMap* tmA2, const int mb, const int rw, const uint32_t tag) {
  const int lane = threadIdx.x & 31, q = lane & 3;
  const int t = mb >> 3, g = mb & 7;
  {
    uint4 v[4];
    uint32_t it = 0;
    while (true) {
      bool ok = true;
#pragma unroll
      for (int k = 0; k < 4; k++) {
        v[k] = ldg_ll(&g_modll[(k * 64 + rw * 32 + lane) * 2]);
        ok = ok && v[k].y == tag && v[k].w == tag;
      }
      if (ok) break;
      if (++it > SPIN_LIMIT) __trap();
    }
#pragma unroll
    for (int k = 0; k < 4; k++) {
      const int pi = ((k & 1) * 64 + rw * 32 + lane) * 2;
      const uint32_t a = SB + SM_MODBUF + (pi >> 3) * 64 + (pi & 3) * 16 + ((pi >> 2) & 1) * 4 + (k < 2 ? 8 : 0);
      asm volatile("st.shared.b32 [%0], %1;" ::"r"(a), "r"(v[k].x) : "memory");
      asm volatile("st.shared.b32 [%0], %1;" ::"r"(a + 16), "r"(v[k].z) : "memory");
    }
    __syncwarp();
    mbar_arrive_pred(SB + MB_MOD, lane);
  }
  unsigned* const cnt = g_cnt + t * 32;
  const int row = t * 128 + g * 16 + (lane >> 2) + (q & 1) * 8;
  const int colb = rw * 64 + (q >> 1) * 8;
  const float piv = __bfloat162float(p.x[row * 512]);
  const uint4* const src = g_part + (size_t)(t * 8 + g) * 4 * 2048 + rw * 128 + lane;
  float s1 = 0.f, s2 = 0.f;
#pragma unroll 1
  for (int e = 0; e < 8; e++) {
    const int c = e & 3;
    mbar_wait(SB + MB_PST + 8 * e, 0);
    if (e == 0) {
      if (lane == 0) wait_cnt(g_cnt + 16 * 32, tag * NHELP);
      __syncwarp();
      const int i = rw * 32 + lane;
      uint4 a = ldg_cg(&g_uv[g * 112 + i]);
      sts128(SB + SM_MODBUF + i * 16, a.x, a.y, a.z, a.w);
      if (i < 48) {
        a = ldg_cg(&g_uv[g * 112 + 64 + i]);
        sts128(SB + SM_MODBUF + (64 + i) * 16, a.x, a.y, a.z, a.w);
      }
    }
    if (e == 3) mbar_wait(SB + MB_SLOT0, 0);
    if (lane == 0) wait_cnt(cnt + e, tag * 8);
    __syncwarp();
    if (rw == 0 && lane == 0) TS(2, 2 * e);
    const uint32_t slot = SB + SM_STASH + (c == 3 ? 0 : c) * 32768;
    const uint32_t stg = slot + rw * 2048 + lane * 16;
#pragma unroll
    for (int i = 0; i < 4; i++) {
#pragma unroll
      for (int s = 0; s < 8; s++) cp_async16(stg + s * 4096 + i * 512, src + c * 2048 + s * 256 + i * 32);
      cp_commit();
    }
    const int col = c * 128 + colb, off = row * 512 + col;
    if (e < 4) {
      ex1_slot<0>(p, stg, q, off, col, piv, s1, s2);
      ex1_slot<1>(p, stg, q, off, col, piv, s1, s2);
      ex1_slot<2>(p, stg, q, off, col, piv, s1, s2);
      ex1_slot<3>(p, stg, q, off, col, piv, s1, s2);
      if (e == 3) {
        s1 += __shfl_xor_sync(0xffffffffu, s1, 2);
        s2 += __shfl_xor_sync(0xffffffffu, s2, 2);
        if (q < 2) stg128(&g_st2[row * 2 + rw], __float_as_uint(s1), __float_as_uint(s2), __float_as_uint(piv), 0);
      }
      __syncwarp();
      if (lane == 0) {
        if (rw == 0) TS(2, 2 * e + 1);
        signal_cnt(cnt + 8 + c);
        if (rw == 0) {
          wait_cnt(cnt + 8 + c, tag * 16);
          asm volatile("fence.proxy.async;" ::: "memory");
          mbar_expect_tx(SB + MB_A2 + 8 * c, 32768);
          tma3d(slot, tmA2, SB + MB_A2 + 8 * c, 0, t * 128, 2 * c);
          TS(2, 16 + e);
        }
      }
      __syncwarp();
    } else {
      ex2_slot<0>(p, stg, q, off, col);
      ex2_slot<1>(p, stg, q, off, col);
      ex2_slot<2>(p, stg, q, off, col);
      ex2_slot<3>(p, stg, q, off, col);
      if (rw == 0 && lane == 0) TS(2, 2 * e + 1);
    }
  }
  if (rw == 0 && lane == 0) g_epoch[blockIdx.x * 8] = tag;
}

__device__ __noinline__ void helper_cta(const Params& p, uint8_t* smem) {
  const int tid = threadIdx.x, hb = blockIdx.x;
  float* sc = (float*)smem;
  float* red = sc + 512;
  float* vec = red + 6 * 448 * 2;
  for (int i = tid; i < 512; i += NTHREADS) {
    const float c = __bfloat162float(p.c[i]);
    sc[i] = bf_round(c / (1.0f + __expf(-c)));
  }
  __syncthreads();
  if (tid < 320) {
    const int v = tid % 160, rg = tid / 160;
    const int col = v < 128 ? 1536 + v * 8 : (v < 144 ? 1024 + hb * 128 + (v - 128) * 8 : 2560 + hb * 128 + (v - 144) * 8);
    float a[8] = {0.f, 0.f, 0.f, 0.f, 0.f, 0.f, 0.f, 0.f};
#pragma unroll 1
    for (int k0 = rg * 256; k0 < rg * 256 + 256; k0 += 16) {
      uint4 w[16];
#pragma unroll
      for (int i = 0; i < 16; i++) w[i] = ldg_nc(p.wmod + (size_t)(k0 + i) * 3072 + col);
#pragma unroll
      for (int i = 0; i < 16; i++) {
        const float s = sc[k0 + i];
        a[0] = fmaf(s, bf_lo(w[i].x), a[0]); a[1] = fmaf(s, bf_hi(w[i].x), a[1]);
        a[2] = fmaf(s, bf_lo(w[i].y), a[2]); a[3] = fmaf(s, bf_hi(w[i].y), a[3]);
        a[4] = fmaf(s, bf_lo(w[i].z), a[4]); a[5] = fmaf(s, bf_hi(w[i].z), a[5]);
        a[6] = fmaf(s, bf_lo(w[i].w), a[6]); a[7] = fmaf(s, bf_hi(w[i].w), a[7]);
      }
    }
#pragma unroll
    for (int i = 0; i < 8; i++) red[rg * 1280 + v * 8 + i] = a[i];
  }
  __syncthreads();
  for (int i = tid; i < 1280; i += NTHREADS) {
    float v = bf_round(red[i] + red[1280 + i]);
    if (i < 1024) {
      if (i >= 512) {
        v = bf_round(1.0f + v);
        if (((i - 512) >> 7) == hb) g_vec[i] = __float2bfloat16_rn(v);
      }
      vec[i] = v;
    } else if (i < 1152) {
      g_vec[hb * 128 + i - 1024] = __float2bfloat16_rn(v);
    } else {
      g_vec[1024 + hb * 128 + i - 1152] = __float2bfloat16_rn(v);
    }
  }
  __syncthreads();
  if (tid < 336) {
    const int v = tid % 56, rg = tid / 56;
    float u[8] = {0.f, 0.f, 0.f, 0.f, 0.f, 0.f, 0.f, 0.f}, w2[8] = {0.f, 0.f, 0.f, 0.f, 0.f, 0.f, 0.f, 0.f};
#pragma unroll 1
    for (int k0 = rg * 16; k0 < 512; k0 += 96) {
      uint4 w[16];
#pragma unroll
      for (int i = 0; i < 16; i++) w[i] = ldg_nc(p.w1 + (size_t)(k0 + i) * 1792 + hb * 448 + v * 8);
#pragma unroll
      for (int i = 0; i < 16; i++) {
        const float sbv = vec[k0 + i], cbv = vec[512 + k0 + i];
        const float f[8] = {bf_lo(w[i].x), bf_hi(w[i].x), bf_lo(w[i].y), bf_hi(w[i].y), bf_lo(w[i].z), bf_hi(w[i].z), bf_lo(w[i].w), bf_hi(w[i].w)};
#pragma unroll
        for (int e = 0; e < 8; e++) { u[e] = fmaf(cbv, f[e], u[e]); w2[e] = fmaf(sbv, f[e], w2[e]); }
      }
    }
#pragma unroll
    for (int e = 0; e < 8; e++) { red[(rg * 448 + v * 8 + e) * 2] = u[e]; red[(rg * 448 + v * 8 + e) * 2 + 1] = w2[e]; }
  }
  __syncthreads();
  if (tid < 224) {
    float4 r = make_float4(0.f, 0.f, 0.f, 0.f);
#pragma unroll
    for (int k = 0; k < 6; k++) {
      const float4 a = *(const float4*)&red[(k * 448 + tid * 2) * 2];
      r.x += a.x; r.z += a.y; r.y += a.z; r.w += a.w;
    }
    r.z *= 0.5f; r.w *= 0.5f;
    g_uv[hb * 224 + tid] = r;
  }
  __syncthreads();
  if (tid == 0) { signal_cnt(g_cnt + 16 * 32); TS(0, 1); }
}

__global__ void __launch_bounds__(NTHREADS, 1)
fused_block_kernel(const __grid_constant__ CUtensorMap tmX, const __grid_constant__ CUtensorMap tmWq,
                   const __grid_constant__ CUtensorMap tmK, const __grid_constant__ CUtensorMap tmV,
                   const __grid_constant__ CUtensorMap tmWo, const __grid_constant__ CUtensorMap tmW1,
                   const __grid_constant__ CUtensorMap tmW2, const __grid_constant__ CUtensorMap tmA2,
                   const __grid_constant__ Params p) {
  extern __shared__ __align__(1024) uint8_t smem_raw[];
  if (blockIdx.x < NHELP) {
    if (threadIdx.x == 0) TS(0, 0);
    helper_cta(p, smem_raw);
    return;
  }
  const int mb = blockIdx.x - NHELP;
  if (threadIdx.x < 256) {
    asm volatile("setmaxnreg.inc.sync.aligned.u32 224;");
    consumer(p, mb);
  } else {
    asm volatile("setmaxnreg.dec.sync.aligned.u32 56;");
    const int warp = threadIdx.x >> 5, lane = threadIdx.x & 31;
    if (warp == 8) {
      if (lane == 0) {
        if ((uint32_t)__cvta_generic_to_shared(smem_raw) != SB) __trap();
        prefetch_tmap(&tmX); prefetch_tmap(&tmWq);
        for (int s = 0; s < 4; s++) { mbar_init(FULLB(s), 1); mbar_init(EMPTYB(s), 8); mbar_init(SB + MB_A2 + 8 * s, 1); }
        for (int s = 0; s < 3; s++) mbar_init(SB + MB_XFULL + 8 * s, 1);
        for (int s = 0; s < 8; s++) mbar_init(SB + MB_PST + 8 * s, 8);
        mbar_init(SB + MB_MOD, 2);
        mbar_init(SB + MB_SLOT0, 8);
        asm volatile("fence.mbarrier_init.release.cluster;\nfence.proxy.async;" ::: "memory");
      }
      __syncwarp();
      bar_arrive(0, NTHREADS);
      if (lane == 0) producer(&tmX, &tmWq, &tmK, &tmV, &tmWo, &tmW1, &tmW2, mb);
    } else {
      uint32_t tag;
      asm volatile("ld.relaxed.gpu.global.u32 %0, [%1];" : "=r"(tag) : "l"(&g_epoch[blockIdx.x * 8]) : "memory");
      tag += 1;
      bar_sync(0, NTHREADS);
      if (warp < 11) {
        reducer(p, &tmA2, mb, warp - 9, tag);
      } else if (lane == 0) {
        prefetch_tmap(&tmK); prefetch_tmap(&tmV); prefetch_tmap(&tmWo); prefetch_tmap(&tmW1); prefetch_tmap(&tmW2); prefetch_tmap(&tmA2);
        unsigned* const cnt = g_cnt + (mb >> 3) * 32;
#pragma unroll 1
        for (int e = 0; e < 8; e++) {
          mbar_wait(SB + MB_PST + 8 * e, 0);
          TS(3, 2 * e);
          signal_cnt(cnt + e);
          TS(3, 2 * e + 1);
        }
      }
    }
  }
}

typedef CUresult (*EncodeFn)(CUtensorMap*, CUtensorMapDataType, cuuint32_t, void*, const cuuint64_t*, const cuuint64_t*,
                             const cuuint32_t*, const cuuint32_t*, CUtensorMapInterleave, CUtensorMapSwizzle,
                             CUtensorMapL2promotion, CUtensorMapFloatOOBfill);

void make_map3(EncodeFn enc, CUtensorMap* m, const void* ptr, int rows, int cols, int box_rows) {
  cuuint64_t dims[3] = {64, (cuuint64_t)rows, (cuuint64_t)(cols / 64)};
  cuuint64_t strides[2] = {(cuuint64_t)cols * 2, 128};
  cuuint32_t box[3] = {64, (cuuint32_t)box_rows, 2};
  cuuint32_t es[3] = {1, 1, 1};
  enc(m, CU_TENSOR_MAP_DATA_TYPE_BFLOAT16, 3, const_cast<void*>(ptr), dims, strides, box, es, CU_TENSOR_MAP_INTERLEAVE_NONE,
      CU_TENSOR_MAP_SWIZZLE_128B, CU_TENSOR_MAP_L2_PROMOTION_L2_256B, CU_TENSOR_MAP_FLOAT_OOB_FILL_NONE);
}

}

extern "C" void kernel_launch(void* const* d_in, const int* in_sizes, int n_in, void* d_out, int out_size) {
  (void)in_sizes; (void)n_in; (void)out_size;
  void* fn = nullptr;
  cudaDriverEntryPointQueryResult qr;
  cudaGetDriverEntryPoint("cuTensorMapEncodeTiled", &fn, cudaEnableDefault, &qr);
  EncodeFn enc = (EncodeFn)fn;
  void* a2 = nullptr;
  cudaGetSymbolAddress(&a2, g_a2);
  CUtensorMap tmX, tmWq, tmK, tmV, tmWo, tmW1, tmW2, tmA2;
  make_map3(enc, &tmX, d_in[0], 2048, 512, 64);
  make_map3(enc, &tmK, d_in[1], 16384, 128, 128);
  make_map3(enc, &tmV, d_in[2], 16384, 128, 128);
  make_map3(enc, &tmWq, d_in[3], 512, 4096, 128);
  make_map3(enc, &tmWo, d_in[4], 4096, 512, 128);
  make_map3(enc, &tmW2, d_in[7], 1792, 512, 112);
  make_map3(enc, &tmA2, a2, 2048, 512, 128);
  {
    cuuint64_t dims[2] = {1792, 512};
    cuuint64_t strides[1] = {1792 * 2};
    cuuint32_t box[2] = {64, 64};
    cuuint32_t es[2] = {1, 1};
    enc(&tmW1, CU_TENSOR_MAP_DATA_TYPE_BFLOAT16, 2, d_in[6], dims, strides, box, es, CU_TENSOR_MAP_INTERLEAVE_NONE,
        CU_TENSOR_MAP_SWIZZLE_128B, CU_TENSOR_MAP_L2_PROMOTION_L2_256B, CU_TENSOR_MAP_FLOAT_OOB_FILL_NONE);
  }
  Params p;
  p.x = (const __nv_bfloat16*)d_in[0];
  p.c = (const __nv_bfloat16*)d_in[8];
  p.wmod = (const __nv_bfloat16*)d_in[9];
  p.w1 = (const __nv_bfloat16*)d_in[6];
  p.out = (__nv_bfloat16*)d_out;
  cudaFuncSetAttribute(fused_block_kernel, cudaFuncAttributeMaxDynamicSharedMemorySize, SM_TOTAL);
  fused_block_kernel<<<128 + NHELP, NTHREADS, SM_TOTAL>>>(tmX, tmWq, tmK, tmV, tmWo, tmW1, tmW2, tmA2, p);
}
```

```cpp
#include <cuda_runtime.h>
#include <cuda_bf16.h>
#include <cuda.h>
#include <stdint.h>

namespace {

constexpr int NHELP = 4;
constexpr int NTHREADS = 512;
#define MAPMODE 0
#define PFMODE 10
#define PFD1 1000
#define PFD2 2000
#define PFD3 6000
#define XDELAY 0
#define NPRE 2
#define GO_AT 1

constexpr uint32_t SM_STASH = 0;
constexpr uint32_t SM_RING = 98304;
constexpr uint32_t SM_MISC = 229376;
constexpr uint32_t SM_TOTAL = 232448;
constexpr uint32_t MB_FULL = SM_MISC + 0;
constexpr uint32_t MB_EMPTY = SM_MISC + 32;
constexpr uint32_t MB_XFULL = SM_MISC + 64;
constexpr uint32_t MB_GO = SM_MISC + 88;
constexpr uint32_t MB_A2 = SM_MISC + 96;
constexpr uint32_t MB_RFULL = SM_MISC + 144;
constexpr uint32_t MB_XRES = SM_MISC + 176;
constexpr uint32_t MB_LATE = SM_MISC + 184;
constexpr uint32_t MB_RED = SM_MISC + 192;
constexpr uint32_t MB_CLR = SM_MISC + 224;
constexpr uint32_t MB_CREDIT = SM_MISC + 232;
constexpr uint32_t MB_SENT = SM_MISC + 240;
constexpr uint32_t MB_SLOTFREE = SM_MISC + 304;
constexpr int NBARS = 39;
constexpr uint32_t SM_MODBUF = SM_MISC + 512;
constexpr uint32_t SM_STAT = SM_STASH + 3 * 16384 + 2048;
constexpr uint32_t SM_DBG = SM_MISC + 2560;
constexpr uint32_t SB = 1024;
constexpr uint32_t PEER = 1u << 24;

struct __align__(1024) Scratch {
  uint4 part[16 * 4 * 8 * 8 * 128];
  uint4 a2[16 * 8 * 1024];
  uint32_t modp[4 * 1024];
  uint4 st1[2048];
  uint4 st2[2048];
  float4 uv[896];
  __nv_bfloat16 vec[4 * 512];
  unsigned cnt[2 * 32];
  unsigned epoch[132 * 8];
};
__device__ Scratch g_scratch;
#define TS(i) do {} while (0)
#define TSC(i) do {} while (0)
#define TG(i) do {} while (0)
#define TSDUMP(lo, hi) do {} while (0)

constexpr uint32_t SPIN_LIMIT = 1u << 22;

__device__ __forceinline__ void mbar_init(uint32_t bar, uint32_t cnt) {
  asm volatile("mbarrier.init.shared::cta.b64 [%0], %1;" ::"r"(bar), "r"(cnt) : "memory");
}
__device__ __forceinline__ void mbar_expect_tx(uint32_t bar, uint32_t bytes) {
  asm volatile("mbarrier.arrive.expect_tx.shared::cta.b64 _, [%0], %1;" ::"r"(bar), "r"(bytes) : "memory");
}
__device__ __forceinline__ bool elect_one() {
  uint32_t r;
  asm volatile("{\n.reg .pred p;\nelect.sync _|p, 0xffffffff;\nselp.u32 %0, 1, 0, p;\n}" : "=r"(r));
  return r;
}
__device__ __forceinline__ void mbar_arrive_warp(uint32_t bar) {
  asm volatile("{\n.reg .pred p;\nelect.sync _|p, 0xffffffff;\n@p mbarrier.arrive.shared::cta.b64 _, [%0];\n}" ::"r"(bar) : "memory");
}
__device__ __forceinline__ uint32_t keep(uint32_t v) { return __shfl_sync(0xffffffffu, v, threadIdx.x & 31); }
template <class T> __device__ __forceinline__ T* keep(T* p) {
  const uint64_t v = (uint64_t)p;
  return (T*)(((uint64_t)keep((uint32_t)(v >> 32)) << 32) | keep((uint32_t)v));
}
__device__ __forceinline__ void mbar_wait(uint32_t bar, uint32_t parity) {
  asm volatile(
      "{\n.reg .pred p;\n.reg .u32 c;\n"
      "mov.u32 c, 0;\n"
      "LOOP:\n"
      "mbarrier.try_wait.parity.shared::cta.b64 p, [%0], %1;\n"
      "@p bra DONE;\n"
      "add.u32 c, c, 1;\n"
      "setp.lt.u32 p, c, %2;\n"
      "@p bra LOOP;\n"
      "trap;\n"
      "DONE:\n}" ::"r"(bar), "r"(parity), "n"(SPIN_LIMIT) : "memory");
}
__device__ __forceinline__ void mbar_spin(uint32_t bar, uint32_t parity) {
  asm volatile("{\n.reg .pred p;\nLOOP:\nmbarrier.try_wait.parity.shared::cta.b64 p, [%0], %1;\n@!p bra LOOP;\n}" ::"r"(bar), "r"(parity) : "memory");
}
__device__ __forceinline__ void bar_sync(uint32_t id, uint32_t n) { asm volatile("bar.sync %0, %1;" ::"r"(id), "r"(n) : "memory"); }
__device__ __forceinline__ void bar_arrive(uint32_t id, uint32_t n) { asm volatile("bar.arrive %0, %1;" ::"r"(id), "r"(n) : "memory"); }
__device__ __forceinline__ void tma3d(uint32_t dst, const CUtensorMap* m, uint32_t bar, int c0, int c1, int c2) {
  asm volatile("cp.async.bulk.tensor.3d.shared::cluster.global.mbarrier::complete_tx::bytes [%0], [%1, {%3, %4, %5}], [%2];"
               ::"r"(dst), "l"(m), "r"(bar), "r"(c0), "r"(c1), "r"(c2) : "memory");
}
__device__ __forceinline__ void tma3d_mc(uint32_t dst, const CUtensorMap* m, uint32_t bar, int c0, int c1, int c2) {
  asm volatile("cp.async.bulk.tensor.3d.shared::cluster.global.mbarrier::complete_tx::bytes.multicast::cluster [%0], [%1, {%3, %4, %5}], [%2], %6;"
               ::"r"(dst), "l"(m), "r"(bar), "r"(c0), "r"(c1), "r"(c2), "h"((uint16_t)3) : "memory");
}
__device__ __forceinline__ void bulk_load_mc(uint32_t dst, const void* src, uint32_t bytes, uint32_t bar) {
  asm volatile("cp.async.bulk.shared::cluster.global.mbarrier::complete_tx::bytes.multicast::cluster [%0], [%1], %2, [%3], %4;"
               ::"r"(dst), "l"(src), "r"(bytes), "r"(bar), "h"((uint16_t)3) : "memory");
}
__device__ __forceinline__ unsigned ld_cnt(const unsigned* p) {
  unsigned v; asm volatile("ld.relaxed.gpu.global.u32 %0, [%1];" : "=r"(v) : "l"(p) : "memory"); return v;
}
__device__ __forceinline__ void prefetch_tmap(const CUtensorMap* m) {
  asm volatile("prefetch.tensormap [%0];" ::"l"(m) : "memory");
}
__device__ __forceinline__ void wg_fence() { asm volatile("wgmma.fence.sync.aligned;" ::: "memory"); }
__device__ __forceinline__ void wg_commit() { asm volatile("wgmma.commit_group.sync.aligned;" ::: "memory"); }
template <int N> __device__ __forceinline__ void wg_wait() { asm volatile("wgmma.wait_group.sync.aligned %0;" ::"n"(N) : "memory"); }
template <int N> __device__ __forceinline__ void pin(float (&d)[N]) {
#pragma unroll
  for (int i = 0; i < N; i++) asm volatile("" : "+f"(d[i])::"memory");
}
template <int N> __device__ __forceinline__ void pin(uint32_t (&d)[N]) {
#pragma unroll
  for (int i = 0; i < N; i++) asm volatile("" : "+r"(d[i])::"memory");
}
__device__ __forceinline__ uint64_t mkdesc(uint32_t addr, uint32_t lbo) {
  uint32_t lo = (addr >> 4) | ((lbo >> 4) << 16);
  return ((uint64_t)0x40000040u << 32) | lo;
}
__device__ __forceinline__ uint32_t pack2(float lo, float hi) {
  uint32_t r;
  asm("cvt.rn.bf16x2.f32 %0, %1, %2;" : "=r"(r) : "f"(hi), "f"(lo));
  return r;
}
__device__ __forceinline__ float bf_lo(uint32_t w) { return __uint_as_float(w << 16); }
__device__ __forceinline__ float bf_hi(uint32_t w) { return __uint_as_float(w & 0xffff0000u); }
__device__ __forceinline__ float bf_round(float x) { return __bfloat162float(__float2bfloat16_rn(x)); }
__device__ __forceinline__ uint32_t bf2_fma(uint32_t a, uint32_t b, uint32_t c) {
  uint32_t r; asm("fma.rn.bf16x2 %0, %1, %2, %3;" : "=r"(r) : "r"(a), "r"(b), "r"(c)); return r;
}
__device__ __forceinline__ uint32_t bf2_mul(uint32_t a, uint32_t b) {
  uint32_t r; asm("mul.rn.bf16x2 %0, %1, %2;" : "=r"(r) : "r"(a), "r"(b)); return r;
}
__device__ __forceinline__ uint32_t bf2_add(uint32_t a, uint32_t b) {
  uint32_t r; asm("add.rn.bf16x2 %0, %1, %2;" : "=r"(r) : "r"(a), "r"(b)); return r;
}
__device__ __forceinline__ float ex2(float x) { float r; asm("ex2.approx.ftz.f32 %0, %1;" : "=f"(r) : "f"(x)); return r; }
__device__ __forceinline__ float rcp_fast(float x) { float r; asm("rcp.approx.ftz.f32 %0, %1;" : "=f"(r) : "f"(x)); return r; }
__device__ __forceinline__ float tanh_hw(float x) { float r; asm("tanh.approx.f32 %0, %1;" : "=f"(r) : "f"(x)); return r; }
__device__ __forceinline__ void sts128(uint32_t a, uint32_t x, uint32_t y, uint32_t z, uint32_t w) {
  asm volatile("st.shared.v4.b32 [%0], {%1, %2, %3, %4};" ::"r"(a), "r"(x), "r"(y), "r"(z), "r"(w) : "memory");
}
__device__ __forceinline__ void lds128(uint32_t a, uint32_t& x, uint32_t& y, uint32_t& z, uint32_t& w) {
  asm volatile("ld.shared.v4.b32 {%0, %1, %2, %3}, [%4];" : "=r"(x), "=r"(y), "=r"(z), "=r"(w) : "r"(a) : "memory");
}
__device__ __forceinline__ void ldsm4(uint32_t a, uint32_t& x, uint32_t& y, uint32_t& z, uint32_t& w) {
  asm volatile("ldmatrix.sync.aligned.m8n8.x4.shared.b16 {%0, %1, %2, %3}, [%4];" : "=r"(x), "=r"(y), "=r"(z), "=r"(w) : "r"(a) : "memory");
}
__device__ __forceinline__ uint4 ldg_nc(const void* p) {
  uint4 v; asm volatile("ld.global.nc.L1::no_allocate.v4.b32 {%0, %1, %2, %3}, [%4];" : "=r"(v.x), "=r"(v.y), "=r"(v.z), "=r"(v.w) : "l"(p)); return v;
}
__device__ __forceinline__ uint4 ldg_cg(const void* p) {
  uint4 v; asm volatile("ld.global.cg.v4.b32 {%0, %1, %2, %3}, [%4];" : "=r"(v.x), "=r"(v.y), "=r"(v.z), "=r"(v.w) : "l"(p) : "memory"); return v;
}
template <int LUT> __device__ __forceinline__ uint32_t lop3(uint32_t a, uint32_t b, uint32_t c) {
  uint32_t r; asm("lop3.b32 %0, %1, %2, %3, %4;" : "=r"(r) : "r"(a), "r"(b), "r"(c), "n"(LUT)); return r;
}
__device__ __forceinline__ uint4 ldg_ll(const void* p) {
  unsigned long long a, b;
  asm volatile("ld.relaxed.gpu.global.v2.b64 {%0, %1}, [%2];" : "=l"(a), "=l"(b) : "l"(p) : "memory");
  return make_uint4((uint32_t)a, (uint32_t)(a >> 32), (uint32_t)b, (uint32_t)(b >> 32));
}
__device__ __forceinline__ void stg_ll(void* p, uint32_t v, uint32_t tag) {
  unsigned long long a = ((unsigned long long)tag << 32) | v;
  asm volatile("st.relaxed.gpu.global.b64 [%0], %1;" ::"l"(p), "l"(a) : "memory");
}
__device__ __forceinline__ uint4 ldg_b128(const void* p) {
  uint4 v; asm volatile("ld.relaxed.gpu.global.v4.b32 {%0, %1, %2, %3}, [%4];" : "=r"(v.x), "=r"(v.y), "=r"(v.z), "=r"(v.w) : "l"(p) : "memory"); return v;
}
template <int TAG> __device__ __forceinline__ void ldg_retry(uint32_t& x, uint32_t& y, uint32_t& z, uint32_t& w, const void* p) {
  asm volatile("{\n.reg .pred p;\n.reg .b32 t;\nand.b32 t, %0, 1;\nsetp.ne.b32 p, t, %5;\n"
               "@p ld.relaxed.gpu.global.v4.b32 {%0, %1, %2, %3}, [%4];\n}" : "+r"(x), "+r"(y), "+r"(z), "+r"(w) : "l"(p), "n"(TAG) : "memory");
}
__device__ __forceinline__ void stg_b128(void* p, uint32_t x, uint32_t y, uint32_t z, uint32_t w) {
  asm volatile("st.relaxed.gpu.global.v4.b32 [%0], {%1, %2, %3, %4};" ::"l"(p), "r"(x), "r"(y), "r"(z), "r"(w) : "memory");
}
__device__ __forceinline__ void stg128(void* p, uint32_t x, uint32_t y, uint32_t z, uint32_t w) {
  asm volatile("st.global.v4.b32 [%0], {%1, %2, %3, %4};" ::"l"(p), "r"(x), "r"(y), "r"(z), "r"(w) : "memory");
}
__device__ __forceinline__ void stsm4(uint32_t a, uint32_t x, uint32_t y, uint32_t z, uint32_t w) {
  asm volatile("stmatrix.sync.aligned.m8n8.x4.shared.b16 [%0], {%1, %2, %3, %4};" ::"r"(a), "r"(x), "r"(y), "r"(z), "r"(w) : "memory");
}
__device__ __forceinline__ void mbar_arrive_remote(uint32_t bar) {
  asm volatile("{\n.reg .pred p;\nelect.sync _|p, 0xffffffff;\n@p mbarrier.arrive.shared::cluster.b64 _, [%0];\n}" ::"r"(bar) : "memory");
}
__device__ __forceinline__ void st_async128(uint32_t a, uint32_t x, uint32_t y, uint32_t z, uint32_t w, uint32_t bar) {
  asm volatile("st.async.weak.shared::cluster.mbarrier::complete_tx::bytes.v4.b32 [%0], {%1, %2, %3, %4}, [%5];"
               ::"r"(a), "r"(x), "r"(y), "r"(z), "r"(w), "r"(bar) : "memory");
}
__device__ __forceinline__ void fence_async_smem() { asm volatile("fence.proxy.async.shared::cta;" ::: "memory"); }
__device__ __forceinline__ void bulk_load(uint32_t dst, const void* src, uint32_t bytes, uint32_t bar) {
  asm volatile("cp.async.bulk.shared::cluster.global.mbarrier::complete_tx::bytes [%0], [%1], %2, [%3];" ::"r"(dst), "l"(src), "r"(bytes), "r"(bar) : "memory");
}
__device__ __forceinline__ void l2_prefetch(const void* p, uint32_t bytes) {
  asm volatile("cp.async.bulk.prefetch.L2.global [%0], %1;" ::"l"(p), "r"(bytes) : "memory");
}
__device__ __forceinline__ void signal_cnt(unsigned* p) {
  asm volatile("fence.acq_rel.gpu;\nred.relaxed.gpu.global.add.u32 [%0], 1;" ::"l"(p) : "memory");
}
__device__ __forceinline__ void wait_cnt(const unsigned* p, unsigned target) {
  unsigned v, it = 0;
  while (true) {
    asm volatile("ld.acquire.gpu.global.u32 %0, [%1];" : "=r"(v) : "l"(p) : "memory");
    if ((int)(v - target) >= 0) break;
    if (++it > SPIN_LIMIT) asm volatile("trap;");
  }
}

#define ACC8(d, i) "+f"(d[i]), "+f"(d[i+1]), "+f"(d[i+2]), "+f"(d[i+3]), "+f"(d[i+4]), "+f"(d[i+5]), "+f"(d[i+6]), "+f"(d[i+7])
__device__ __forceinline__ void wgmma_rs128_k_init(float (&d)[64], uint32_t a0, uint32_t a1, uint32_t a2, uint32_t a3, uint64_t db) {
  asm volatile("{\n"
    "wgmma.mma_async.sync.aligned.m64n128k16.f32.bf16.bf16 {"
    "%0, %1, %2, %3, %4, %5, %6, %7, %8, %9, %10, %11, %12, %13, %14, %15, "
    "%16, %17, %18, %19, %20, %21, %22, %23, %24, %25, %26, %27, %28, %29, %30, %31, "
    "%32, %33, %34, %35, %36, %37, %38, %39, %40, %41, %42, %43, %44, %45, %46, %47, "
    "%48, %49, %50, %51, %52, %53, %54, %55, %56, %57, %58, %59, %60, %61, %62, %63}, "
    "{%64, %65, %66, %67}, %68, 0, 1, 1, 0;\n}"
    : ACC8(d, 0), ACC8(d, 8), ACC8(d, 16), ACC8(d, 24), ACC8(d, 32), ACC8(d, 40), ACC8(d, 48), ACC8(d, 56)
    : "r"(a0), "r"(a1), "r"(a2), "r"(a3), "l"(db));
}

__device__ __forceinline__ void wgmma_rs128_k_acc(float (&d)[64], uint32_t a0, uint32_t a1, uint32_t a2, uint32_t a3, uint64_t db) {
  asm volatile("{\n"
    "wgmma.mma_async.sync.aligned.m64n128k16.f32.bf16.bf16 {"
    "%0, %1, %2, %3, %4, %5, %6, %7, %8, %9, %10, %11, %12, %13, %14, %15, "
    "%16, %17, %18, %19, %20, %21, %22, %23, %24, %25, %26, %27, %28, %29, %30, %31, "
    "%32, %33, %34, %35, %36, %37, %38, %39, %40, %41, %42, %43, %44, %45, %46, %47, "
    "%48, %49, %50, %51, %52, %53, %54, %55, %56, %57, %58, %59, %60, %61, %62, %63}, "
    "{%64, %65, %66, %67}, %68, 1, 1, 1, 0;\n}"
    : ACC8(d, 0), ACC8(d, 8), ACC8(d, 16), ACC8(d, 24), ACC8(d, 32), ACC8(d, 40), ACC8(d, 48), ACC8(d, 56)
    : "r"(a0), "r"(a1), "r"(a2), "r"(a3), "l"(db));
}

__device__ __forceinline__ void wgmma_rs128_mn_init(float (&d)[64], uint32_t a0, uint32_t a1, uint32_t a2, uint32_t a3, uint64_t db) {
  asm volatile("{\n"
    "wgmma.mma_async.sync.aligned.m64n128k16.f32.bf16.bf16 {"
    "%0, %1, %2, %3, %4, %5, %6, %7, %8, %9, %10, %11, %12, %13, %14, %15, "
    "%16, %17, %18, %19, %20, %21, %22, %23, %24, %25, %26, %27, %28, %29, %30, %31, "
    "%32, %33, %34, %35, %36, %37, %38, %39, %40, %41, %42, %43, %44, %45, %46, %47, "
    "%48, %49, %50, %51, %52, %53, %54, %55, %56, %57, %58, %59, %60, %61, %62, %63}, "
    "{%64, %65, %66, %67}, %68, 0, 1, 1, 1;\n}"
    : ACC8(d, 0), ACC8(d, 8), ACC8(d, 16), ACC8(d, 24), ACC8(d, 32), ACC8(d, 40), ACC8(d, 48), ACC8(d, 56)
    : "r"(a0), "r"(a1), "r"(a2), "r"(a3), "l"(db));
}

__device__ __forceinline__ void wgmma_rs128_mn_acc(float (&d)[64], uint32_t a0, uint32_t a1, uint32_t a2, uint32_t a3, uint64_t db) {
  asm volatile("{\n"
    "wgmma.mma_async.sync.aligned.m64n128k16.f32.bf16.bf16 {"
    "%0, %1, %2, %3, %4, %5, %6, %7, %8, %9, %10, %11, %12, %13, %14, %15, "
    "%16, %17, %18, %19, %20, %21, %22, %23, %24, %25, %26, %27, %28, %29, %30, %31, "
    "%32, %33, %34, %35, %36, %37, %38, %39, %40, %41, %42, %43, %44, %45, %46, %47, "
    "%48, %49, %50, %51, %52, %53, %54, %55, %56, %57, %58, %59, %60, %61, %62, %63}, "
    "{%64, %65, %66, %67}, %68, 1, 1, 1, 1;\n}"
    : ACC8(d, 0), ACC8(d, 8), ACC8(d, 16), ACC8(d, 24), ACC8(d, 32), ACC8(d, 40), ACC8(d, 48), ACC8(d, 56)
    : "r"(a0), "r"(a1), "r"(a2), "r"(a3), "l"(db));
}

__device__ __forceinline__ void wgmma_rs128_mn_pred(float (&d)[64], uint32_t a0, uint32_t a1, uint32_t a2, uint32_t a3, uint64_t db, int scale_d) {
  asm volatile("{\n.reg .pred p;\nsetp.ne.b32 p, %69, 0;\n"
    "wgmma.mma_async.sync.aligned.m64n128k16.f32.bf16.bf16 {"
    "%0, %1, %2, %3, %4, %5, %6, %7, %8, %9, %10, %11, %12, %13, %14, %15, "
    "%16, %17, %18, %19, %20, %21, %22, %23, %24, %25, %26, %27, %28, %29, %30, %31, "
    "%32, %33, %34, %35, %36, %37, %38, %39, %40, %41, %42, %43, %44, %45, %46, %47, "
    "%48, %49, %50, %51, %52, %53, %54, %55, %56, %57, %58, %59, %60, %61, %62, %63}, "
    "{%64, %65, %66, %67}, %68, p, 1, 1, 1;\n}"
    : ACC8(d, 0), ACC8(d, 8), ACC8(d, 16), ACC8(d, 24), ACC8(d, 32), ACC8(d, 40), ACC8(d, 48), ACC8(d, 56)
    : "r"(a0), "r"(a1), "r"(a2), "r"(a3), "l"(db), "r"(scale_d));
}

__device__ __forceinline__ void wgmma_rs96_mn_init(float (&d)[48], uint32_t a0, uint32_t a1, uint32_t a2, uint32_t a3, uint64_t db) {
  asm volatile("{\n"
    "wgmma.mma_async.sync.aligned.m64n96k16.f32.bf16.bf16 {"
    "%0, %1, %2, %3, %4, %5, %6, %7, %8, %9, %10, %11, %12, %13, %14, %15, "
    "%16, %17, %18, %19, %20, %21, %22, %23, %24, %25, %26, %27, %28, %29, %30, %31, "
    "%32, %33, %34, %35, %36, %37, %38, %39, %40, %41, %42, %43, %44, %45, %46, %47}, "
    "{%48, %49, %50, %51}, %52, 0, 1, 1, 1;\n}"
    : ACC8(d, 0), ACC8(d, 8), ACC8(d, 16), ACC8(d, 24), ACC8(d, 32), ACC8(d, 40)
    : "r"(a0), "r"(a1), "r"(a2), "r"(a3), "l"(db));
}

__device__ __forceinline__ void wgmma_rs96_mn_acc(float (&d)[48], uint32_t a0, uint32_t a1, uint32_t a2, uint32_t a3, uint64_t db) {
  asm volatile("{\n"
    "wgmma.mma_async.sync.aligned.m64n96k16.f32.bf16.bf16 {"
    "%0, %1, %2, %3, %4, %5, %6, %7, %8, %9, %10, %11, %12, %13, %14, %15, "
    "%16, %17, %18, %19, %20, %21, %22, %23, %24, %25, %26, %27, %28, %29, %30, %31, "
    "%32, %33, %34, %35, %36, %37, %38, %39, %40, %41, %42, %43, %44, %45, %46, %47}, "
    "{%48, %49, %50, %51}, %52, 1, 1, 1, 1;\n}"
    : ACC8(d, 0), ACC8(d, 8), ACC8(d, 16), ACC8(d, 24), ACC8(d, 32), ACC8(d, 40)
    : "r"(a0), "r"(a1), "r"(a2), "r"(a3), "l"(db));
}

__device__ __forceinline__ void wgmma_rs64_mn_init(float (&d)[32], uint32_t a0, uint32_t a1, uint32_t a2, uint32_t a3, uint64_t db) {
  asm volatile("{\n"
    "wgmma.mma_async.sync.aligned.m64n64k16.f32.bf16.bf16 {"
    "%0, %1, %2, %3, %4, %5, %6, %7, %8, %9, %10, %11, %12, %13, %14, %15, "
    "%16, %17, %18, %19, %20, %21, %22, %23, %24, %25, %26, %27, %28, %29, %30, %31}, "
    "{%32, %33, %34, %35}, %36, 0, 1, 1, 1;\n}"
    : ACC8(d, 0), ACC8(d, 8), ACC8(d, 16), ACC8(d, 24)
    : "r"(a0), "r"(a1), "r"(a2), "r"(a3), "l"(db));
}

__device__ __forceinline__ void wgmma_rs64_mn_acc(float (&d)[32], uint32_t a0, uint32_t a1, uint32_t a2, uint32_t a3, uint64_t db) {
  asm volatile("{\n"
    "wgmma.mma_async.sync.aligned.m64n64k16.f32.bf16.bf16 {"
    "%0, %1, %2, %3, %4, %5, %6, %7, %8, %9, %10, %11, %12, %13, %14, %15, "
    "%16, %17, %18, %19, %20, %21, %22, %23, %24, %25, %26, %27, %28, %29, %30, %31}, "
    "{%32, %33, %34, %35}, %36, 1, 1, 1, 1;\n}"
    : ACC8(d, 0), ACC8(d, 8), ACC8(d, 16), ACC8(d, 24)
    : "r"(a0), "r"(a1), "r"(a2), "r"(a3), "l"(db));
}

struct Params {
  const __nv_bfloat16 *x, *k, *v, *wq, *wo, *w1, *w2, *c, *wmod;
  __nv_bfloat16* out;
  Scratch* s;
};

constexpr float SC = 0.08838834764831845f * 1.4426950408889634f;

template <int NK, int AOFF, int FIRST, int NA>
__device__ __forceinline__ void tile_rs_mn(float (&acc)[64], const uint32_t (&A)[NA], uint64_t d, int first_scale = 1) {
  if (FIRST == 0) wgmma_rs128_mn_init(acc, A[AOFF], A[AOFF + 1], A[AOFF + 2], A[AOFF + 3], d);
  if (FIRST == 2) wgmma_rs128_mn_pred(acc, A[AOFF], A[AOFF + 1], A[AOFF + 2], A[AOFF + 3], d, first_scale);
#pragma unroll
  for (int ks = FIRST == 1 ? 0 : 1; ks < NK; ks++)
    wgmma_rs128_mn_acc(acc, A[AOFF + 4 * ks], A[AOFF + 4 * ks + 1], A[AOFF + 4 * ks + 2], A[AOFF + 4 * ks + 3], d + ks * 128);
}
template <int NK, int AOFF, int FIRST, int NA>
__device__ __forceinline__ void tile_rs64_mn(float (&acc)[32], const uint32_t (&A)[NA], uint64_t d) {
  if (FIRST == 0) wgmma_rs64_mn_init(acc, A[AOFF], A[AOFF + 1], A[AOFF + 2], A[AOFF + 3], d);
#pragma unroll
  for (int ks = FIRST == 1 ? 0 : 1; ks < NK; ks++)
    wgmma_rs64_mn_acc(acc, A[AOFF + 4 * ks], A[AOFF + 4 * ks + 1], A[AOFF + 4 * ks + 2], A[AOFF + 4 * ks + 3], d + ks * 128);
}
__device__ __forceinline__ void tile_qk(float (&S)[64], const uint32_t (&Q)[32], uint64_t d) {
  wgmma_rs128_k_init(S, Q[0], Q[1], Q[2], Q[3], d);
#pragma unroll
  for (int ks = 1; ks < 8; ks++)
    wgmma_rs128_k_acc(S, Q[4 * ks], Q[4 * ks + 1], Q[4 * ks + 2], Q[4 * ks + 3], d + (ks >> 2) * 1024 + (ks & 3) * 2);
}

struct LnRow { uint32_t r0, n0, r1, n1; };
template <int QQ>
__device__ __forceinline__ void ln_load(uint32_t (&A)[128], uint32_t base, uint32_t off) {
#pragma unroll
  for (int s = 0; s < 8; s++)
    ldsm4(base + (s >> 2) * 8192 + (off ^ ((s & 3) << 5)), A[QQ * 32 + 4 * s], A[QQ * 32 + 4 * s + 1], A[QQ * 32 + 4 * s + 2], A[QQ * 32 + 4 * s + 3]);
}
template <int QQ>
__device__ __forceinline__ void ln_norm(uint32_t (&A)[128], const LnRow& r) {
#pragma unroll
  for (int i = QQ * 32; i < QQ * 32 + 32; i += 2) {
    A[i] = bf2_mul(bf2_add(A[i], r.n0), r.r0);
    A[i + 1] = bf2_mul(bf2_add(A[i + 1], r.n1), r.r1);
  }
}
template <int QQ>
__device__ __forceinline__ void ln_mod(uint32_t (&A)[128], uint32_t maddr) {
#pragma unroll
  for (int s = 0; s < 8; s++) {
    uint32_t cl, ch, sl, sh;
    lds128(maddr + (QQ * 8 + s) * 64, cl, ch, sl, sh);
    uint32_t* a = &A[QQ * 32 + 4 * s];
    a[0] = bf2_fma(a[0], cl, sl);
    a[1] = bf2_fma(a[1], cl, sl);
    a[2] = bf2_fma(a[2], ch, sh);
    a[3] = bf2_fma(a[3], ch, sh);
  }
}

__device__ __forceinline__ float quad_sum(float v) {
  v += __shfl_xor_sync(0xffffffffu, v, 1);
  v += __shfl_xor_sync(0xffffffffu, v, 2);
  return v;
}

struct Soft { float l0, l1, i0, i1; uint32_t bad; };
__device__ __forceinline__ void softmax_step(float (&S)[64], Soft& f) {
  float s0 = f.l0, s1 = f.l1, t0 = 0.f, t1 = 0.f;
#pragma unroll
  for (int j = 0; j < 64; j += 4) {
    S[j] = ex2(S[j]);
    S[j + 1] = ex2(S[j + 1]);
    S[j + 2] = ex2(S[j + 2]);
    S[j + 3] = ex2(S[j + 3]);
    s0 += S[j];
    s1 += S[j + 2];
    if (j == 0) { t0 = S[1]; t1 = S[3]; } else { t0 += S[j + 1]; t1 += S[j + 3]; }
  }
  f.l0 = s0 + t0;
  f.l1 = s1 + t1;
}
__device__ __forceinline__ void head_end(Soft& f) {
  const float l0 = quad_sum(f.l0), l1 = quad_sum(f.l1);
  constexpr float LO = 5.421010862427522e-20f, HI = 1.8446744073709552e19f;
  if (!(l0 >= LO && l0 <= HI && l1 >= LO && l1 <= HI)) f.bad = 1;
  f.i0 = rcp_fast(l0);
  f.i1 = rcp_fast(l1);
  f.l0 = 0.f; f.l1 = 0.f;
}
__device__ __forceinline__ void scale_acc(float (&acc)[64], float a0, float a1) {
#pragma unroll
  for (int i = 0; i < 64; i += 4) { acc[i] *= a0; acc[i + 1] *= a0; acc[i + 2] *= a1; acc[i + 3] *= a1; }
}
__device__ __forceinline__ void stash_acc(const float (&acc)[64], uint32_t addr) {
#pragma unroll
  for (int i = 0; i < 8; i++)
    sts128(addr + i * 2048, pack2(acc[8 * i], acc[8 * i + 1]), pack2(acc[8 * i + 2], acc[8 * i + 3]),
           pack2(acc[8 * i + 4], acc[8 * i + 5]), pack2(acc[8 * i + 6], acc[8 * i + 7]));
}

template <int S0, int N>
__device__ __forceinline__ void silu_part(const float (&Z)[N], uint32_t (&H)[56], uint32_t uvaddr, float hr0, float nm0, float hr1, float nm1) {
#pragma unroll
  for (int s = S0; s < S0 + N / 8; s++) {
#pragma unroll
    for (int hf = 0; hf < 2; hf++) {
      uint32_t u0, u1, v0, v1;
      lds128(uvaddr + (2 * s + hf) * 64, u0, u1, v0, v1);
      const float* z = &Z[8 * (s - S0) + 4 * hf];
      float a = fmaf(z[0], hr0, fmaf(__uint_as_float(u0), nm0, __uint_as_float(v0)));
      float b = fmaf(z[1], hr0, fmaf(__uint_as_float(u1), nm0, __uint_as_float(v1)));
      float c = fmaf(z[2], hr1, fmaf(__uint_as_float(u0), nm1, __uint_as_float(v0)));
      float d = fmaf(z[3], hr1, fmaf(__uint_as_float(u1), nm1, __uint_as_float(v1)));
      H[4 * s + 2 * hf] = pack2(fmaf(a, tanh_hw(a), a), fmaf(b, tanh_hw(b), b));
      H[4 * s + 2 * hf + 1] = pack2(fmaf(c, tanh_hw(c), c), fmaf(d, tanh_hw(d), d));
    }
  }
}

__device__ __forceinline__ void send_chunk(const uint32_t (&k)[16], uint32_t buf, uint32_t rfull) {
  asm volatile("{\n.reg .pred p;\nelect.sync _|p, 0xffffffff;\n@p mbarrier.arrive.expect_tx.shared::cta.b64 _, [%0], 2048;\n}" ::"r"(rfull) : "memory");
#pragma unroll
  for (int i = 0; i < 4; i++) st_async128((buf ^ PEER) + i * 512, k[4 * i], k[4 * i + 1], k[4 * i + 2], k[4 * i + 3], rfull ^ PEER);
}
__device__ __forceinline__ void send_chunk_bulk(const uint32_t (&k)[16], uint32_t stg, uint32_t buf, uint32_t rfull) {
#pragma unroll
  for (int i = 0; i < 4; i++) sts128(stg + i * 512, k[4 * i], k[4 * i + 1], k[4 * i + 2], k[4 * i + 3]);
  fence_async_smem();
  __syncwarp();
  asm volatile("{\n.reg .pred p;\nelect.sync _|p, 0xffffffff;\n@p mbarrier.arrive.expect_tx.shared::cta.b64 _, [%0], 2048;\n"
               "@p cp.async.bulk.shared::cluster.shared::cta.mbarrier::complete_tx::bytes [%1], [%2], 2048, [%3];\n}"
               ::"r"(rfull), "r"((buf & ~511u) ^ PEER), "r"(stg & ~511u), "r"(rfull ^ PEER) : "memory");
}
template <int OFF, int N>
__device__ __forceinline__ void pack_chunk(const float (&acc)[N], uint32_t (&k)[16]) {
#pragma unroll
  for (int i = 0; i < 16; i++) k[i] = pack2(acc[OFF + 2 * i], acc[OFF + 2 * i + 1]);
}
template <int TAG>
__device__ __forceinline__ void keep_chunk(const uint32_t (&k)[16], uint32_t buf, uint4* dst, uint32_t sent) {
  uint32_t w[16];
#pragma unroll
  for (int i = 0; i < 4; i++) lds128(buf + i * 512, w[4 * i], w[4 * i + 1], w[4 * i + 2], w[4 * i + 3]);
#pragma unroll
  for (int i = 0; i < 4; i++) {
    const uint32_t w0 = bf2_add(w[4 * i], k[4 * i]);
    stg_b128(dst + i * 32, TAG ? w0 | 1 : w0 & ~1u, bf2_add(w[4 * i + 1], k[4 * i + 1]), bf2_add(w[4 * i + 2], k[4 * i + 2]),
             bf2_add(w[4 * i + 3], k[4 * i + 3]));
  }
  mbar_arrive_warp(sent);
}

__device__ __forceinline__ void ln_scalars(float mean, float var, float& rstd, float& mb) {
  mb = bf_round(mean);
  float sd;
  asm("sqrt.approx.f32 %0, %1;" : "=f"(sd) : "f"(bf_round(bf_round(var) + 1e-5f)));
  rstd = rcp_fast(bf_round(sd));
}
__device__ __forceinline__ void poll_stats(const uint4* p, uint32_t tag, uint4 a, uint4 b, float& r0, float& n0, float& r1, float& n1) {
  uint32_t it = 0;
#pragma unroll 1
  while (!__all_sync(0xffffffffu, a.y == tag && a.w == tag && b.y == tag && b.w == tag) && ++it < SPIN_LIMIT) {
    a = ldg_ll(p);
    b = ldg_ll(p + 8);
  }
  r0 = __uint_as_float(a.x); n0 = __uint_as_float(a.z);
  r1 = __uint_as_float(b.x); n1 = __uint_as_float(b.z);
}
__device__ __forceinline__ void poll_stats(const uint4* p, uint32_t tag, float& r0, float& n0, float& r1, float& n1) {
  const uint4 z = make_uint4(0, ~tag, 0, 0);
  poll_stats(p, tag, z, z, r0, n0, r1, n1);
}

#define PRB(id, i) do {} while (0)
#define TURN_BEGIN() bar_sync(1 + wg, 256)
#define TURN_END() bar_arrive(2 - wg, 256)
#define FULLB(s) (sb + MB_FULL + 8 * (s))
#define EMPTYB(s) (sb + MB_EMPTY + 8 * (s))
#define STAGE(s) (sb + SM_RING + 32768 * (s))
#define SDESC(s, lbo) (mkdesc(SB + SM_RING, lbo) + (uint64_t)((s) * 2048))
#define SLOT(s) (sb + SM_STASH + 16384 * (s))
__host__ __device__ constexpr int N_W1(int k) { return 49 + 16 + k; }
__host__ __device__ constexpr int N_W2(int k) { return 49 + 24 + k; }

__device__ __forceinline__ void mma16816(float* d, const uint32_t* a, uint32_t b0, uint32_t b1) {
  asm volatile("mma.sync.aligned.m16n8k16.row.col.f32.bf16.bf16.f32 {%0, %1, %2, %3}, {%4, %5, %6, %7}, {%8, %9}, {%0, %1, %2, %3};"
               : "+f"(d[0]), "+f"(d[1]), "+f"(d[2]), "+f"(d[3]) : "r"(a[0]), "r"(a[1]), "r"(a[2]), "r"(a[3]), "r"(b0), "r"(b1));
}
__device__ __forceinline__ void slow_head(const Params& p, uint32_t* out, const int row0, const int head, const uint32_t sb) {
  const int lane = threadIdx.x & 31, q = lane & 3, r = lane >> 2;
  const uint4 sa = ldg_ll(&p.s->st1[row0]), sc = ldg_ll(&p.s->st1[row0 + 8]);
  const LnRow ln = {sa.x, sa.z, sc.x, sc.z};
  float acc[64];
#pragma unroll
  for (int i = 0; i < 64; i++) acc[i] = 0.f;
#pragma unroll 1
  for (int ks = 0; ks < 32; ks++) {
    const uint32_t* xp = (const uint32_t*)(p.x + row0 * 512 + ks * 16 + 2 * q);
    uint32_t a[4] = {xp[0], xp[2048], xp[4], xp[2052]}, cl, ch, sl, sh;
    lds128(sb + SM_MODBUF + q * 16 + ks * 64, cl, ch, sl, sh);
#pragma unroll
    for (int i = 0; i < 4; i++) {
      a[i] = bf2_mul(bf2_add(a[i], (i & 1) ? ln.n1 : ln.n0), (i & 1) ? ln.r1 : ln.r0);
      a[i] = bf2_fma(a[i], (i & 2) ? ch : cl, (i & 2) ? sh : sl);
    }
    const unsigned short* w = (const unsigned short*)p.wq + (ks * 16 + 2 * q) * 4096 + head * 128 + r;
#pragma unroll
    for (int j = 0; j < 16; j++)
      mma16816(&acc[4 * j], a, w[8 * j] | ((uint32_t)w[4096 + 8 * j] << 16), w[8 * 4096 + 8 * j] | ((uint32_t)w[9 * 4096 + 8 * j] << 16));
  }
  uint32_t Q[32];
#pragma unroll
  for (int i = 0; i < 32; i++) { Q[i] = pack2(acc[2 * i], acc[2 * i + 1]); }
#pragma unroll
  for (int i = 0; i < 64; i++) acc[i] = 0.f;
  float m0 = -INFINITY, m1 = -INFINITY, l0 = 0.f, l1 = 0.f;
#pragma unroll 1
  for (int kb = 0; kb < 32; kb++) {
    const int key0 = (head >> 2) * 2048 + 1536 + kb * 16;
    float S[8] = {0.f, 0.f, 0.f, 0.f, 0.f, 0.f, 0.f, 0.f};
    const uint32_t* kp = (const uint32_t*)(p.k + (key0 + r) * 128 + 2 * q);
#pragma unroll
    for (int s2 = 0; s2 < 8; s2++) {
      mma16816(&S[0], &Q[4 * s2], kp[8 * s2], kp[8 * s2 + 4]);
      mma16816(&S[4], &Q[4 * s2], kp[512 + 8 * s2], kp[512 + 8 * s2 + 4]);
    }
    float a0 = fmaxf(fmaxf(S[0], S[1]), fmaxf(S[4], S[5])), a1 = fmaxf(fmaxf(S[2], S[3]), fmaxf(S[6], S[7]));
    a0 = fmaxf(a0, __shfl_xor_sync(0xffffffffu, a0, 1)); a1 = fmaxf(a1, __shfl_xor_sync(0xffffffffu, a1, 1));
    a0 = fmaxf(a0, __shfl_xor_sync(0xffffffffu, a0, 2)); a1 = fmaxf(a1, __shfl_xor_sync(0xffffffffu, a1, 2));
    a0 = fmaxf(a0, m0); a1 = fmaxf(a1, m1);
    const float f0 = ex2(m0 - a0), f1 = ex2(m1 - a1);
    m0 = a0; m1 = a1;
#pragma unroll
    for (int i = 0; i < 8; i++) S[i] = ex2(S[i] - ((i & 2) ? a1 : a0));
    l0 = fmaf(l0, f0, (S[0] + S[1]) + (S[4] + S[5]));
    l1 = fmaf(l1, f1, (S[2] + S[3]) + (S[6] + S[7]));
    scale_acc(acc, f0, f1);
    const uint32_t P[4] = {pack2(S[0], S[1]), pack2(S[2], S[3]), pack2(S[4], S[5]), pack2(S[6], S[7])};
    const unsigned short* v = (const unsigned short*)p.v + (key0 + 2 * q) * 128 + r;
#pragma unroll
    for (int j = 0; j < 16; j++)
      mma16816(&acc[4 * j], P, v[8 * j] | ((uint32_t)v[128 + 8 * j] << 16), v[8 * 128 + 8 * j] | ((uint32_t)v[9 * 128 + 8 * j] << 16));
  }
  scale_acc(acc, rcp_fast(quad_sum(l0)), rcp_fast(quad_sum(l1)));
#pragma unroll
  for (int i = 0; i < 32; i++) out[i] = pack2(acc[2 * i], acc[2 * i + 1]);
}

__device__ __noinline__ void slow_heads(const Params& p, uint32_t* out, const int row0, const int g, const uint32_t sb) {
#pragma unroll 1
  for (int h = 0; h < 4; h++) slow_head(p, out + 32 * h, row0, g * 4 + h, sb);
}

__device__ __forceinline__ void front(const Params& p, uint32_t (&AO)[128], float (&acc)[64], const uint32_t tag, const int row0, const int wg, const int g,
                                      const uint32_t sb) {
  const int tid = threadIdx.x, warp = tid >> 5;
  const uint32_t lane = tid & 31;
  const uint32_t stash = keep(sb + SM_STASH + wg * 49152 + (tid & 127) * 16);
  uint32_t Q[32];
  {
    uint4 v[4];
    const uint32_t* mp = &p.s->modp[tid * 4];
    const uint4 sa = ldg_ll(&p.s->st1[row0]), sc = ldg_ll(&p.s->st1[row0 + 8]);
#pragma unroll
    for (int k = 0; k < 4; k++) v[k] = ldg_b128(mp + k * 1024);
    uint32_t A[128];
    const uint32_t xrow = ((warp & 3) * 16 + (lane & 15)) * 128 + (((lane >> 4) ^ (lane & 7)) << 4);
    const uint32_t maddr = sb + SM_MODBUF + (lane & 3) * 16;
    mbar_spin(FULLB(0), 0);
    ln_load<0>(A, STAGE(0) + wg * 16384, xrow);
    mbar_spin(sb + MB_XFULL, 0);
    ln_load<1>(A, sb + SM_STASH + wg * 49152, xrow);
    ln_load<2>(A, sb + SM_STASH + wg * 49152 + 16384, xrow);
    ln_load<3>(A, sb + SM_STASH + wg * 49152 + 32768, xrow);
    mbar_arrive_warp(EMPTYB(0));
    TSC(20);
    LnRow r;
    {
      float r0, n0, r1, n1;
      poll_stats(&p.s->st1[row0], tag, sa, sc, r0, n0, r1, n1);
      r = {__float_as_uint(r0), __float_as_uint(n0), __float_as_uint(r1), __float_as_uint(n1)};
    }
    TSC(2);
#pragma unroll
    for (int k = 0; k < 4; k++)
      if (((v[k].x ^ tag) | (v[k].w ^ tag)) & 7) v[k] = ldg_b128(mp + k * 1024);
    ln_norm<0>(A, r);
    if (NPRE > 1) ln_norm<1>(A, r);
    if (NPRE > 2) ln_norm<2>(A, r);
    if (NPRE > 3) ln_norm<3>(A, r);
    pin(A);
    PRB(3, 33);
    {
      uint32_t it = 0;
#pragma unroll 1
      while (true) {
        uint32_t bad = 0;
#pragma unroll
        for (int k = 0; k < 4; k++) bad |= (v[k].x ^ tag) | (v[k].w ^ tag);
        if (__all_sync(0xffffffffu, !(bad & 7)) || ++it > SPIN_LIMIT) break;
#pragma unroll
        for (int k = 0; k < 4; k++)
          if (((v[k].x ^ tag) | (v[k].w ^ tag)) & 7) v[k] = ldg_b128(mp + k * 1024);
      }
#pragma unroll
      for (int k = 0; k < 4; k++) { v[k].x &= ~7u; v[k].y &= ~7u; v[k].z &= ~7u; v[k].w &= ~7u; }
      mbar_arrive_warp(sb + MB_GO);
      float m[4];
      m[0] = bf_round((__uint_as_float(v[0].x) + __uint_as_float(v[1].x)) + (__uint_as_float(v[2].x) + __uint_as_float(v[3].x)));
      m[1] = bf_round((__uint_as_float(v[0].y) + __uint_as_float(v[1].y)) + (__uint_as_float(v[2].y) + __uint_as_float(v[3].y)));
      m[2] = bf_round((__uint_as_float(v[0].z) + __uint_as_float(v[1].z)) + (__uint_as_float(v[2].z) + __uint_as_float(v[3].z)));
      m[3] = bf_round((__uint_as_float(v[0].w) + __uint_as_float(v[1].w)) + (__uint_as_float(v[2].w) + __uint_as_float(v[3].w)));
      const float mul = wg ? 1.0f : SC, add = wg ? 1.0f : 0.0f;
      const int pi = (tid & 127) * 2;
      const uint32_t a = sb + SM_MODBUF + (pi >> 3) * 64 + (pi & 3) * 16 + ((pi >> 2) & 1) * 4 + (wg ? 0 : 8);
      asm volatile("st.shared.b32 [%0], %1;" ::"r"(a), "r"(pack2(fmaf(m[0], mul, add), fmaf(m[1], mul, add))) : "memory");
      asm volatile("st.shared.b32 [%0], %1;" ::"r"(a + 16), "r"(pack2(fmaf(m[2], mul, add), fmaf(m[3], mul, add))) : "memory");
    }
    TSC(3);
    bar_sync(4, 256);
    TSC(4); TG(121);
    ln_mod<0>(A, maddr);
#define QSTEP0(KT)                                                                   \
    if (KT == 0) mbar_spin(FULLB(1), 0);                                             \
    PRB(3, 8 + 6 * KT);                                                              \
    TURN_BEGIN();                                                                    \
    pin(A);                                                                          \
    wg_fence();                                                                      \
    tile_rs_mn<8, KT * 32, KT != 0>(acc, A, SDESC((1 + KT) & 3, 16384));             \
    wg_commit();                                                                     \
    TURN_END();                                                                      \
    PRB(3, 9 + 6 * KT);                                                              \
    if (KT < 3) {                                                                    \
      if (KT + 1 >= NPRE) ln_norm<(KT + 1) & 3>(A, r);                               \
      ln_mod<(KT + 1) & 3>(A, maddr);                                                \
      pin(A);                                                                        \
      PRB(3, 11 + 6 * KT);                                                           \
      mbar_spin(FULLB((2 + KT) & 3), KT == 2);                                       \
      PRB(3, 12 + 6 * KT);                                                           \
    }                                                                                \
    wg_wait<0>();                                                                    \
    PRB(3, 13 + 6 * KT);                                                             \
    mbar_arrive_warp(EMPTYB((1 + KT) & 3));
    QSTEP0(0) QSTEP0(1) QSTEP0(2) QSTEP0(3)
#undef QSTEP0
    TSC(5);
#pragma unroll 1
    for (int j = 0; j < 3; j++) {
      pin(acc);
      stash_acc(acc, stash + j * 16384);
#define QSTEP(KT)                                                                    \
      mbar_spin(FULLB((1 + KT) & 3), ((j + 1 + (KT == 3)) & 1))       ;              \
      TURN_BEGIN();                                                                  \
      wg_fence();                                                                    \
      tile_rs_mn<8, KT * 32, KT != 0>(acc, A, SDESC((1 + KT) & 3, 16384));           \
      wg_commit();                                                                   \
      TURN_END();                                                                    \
      wg_wait<0>();                                                                  \
      mbar_arrive_warp(EMPTYB((1 + KT) & 3));
      QSTEP(0) QSTEP(1) QSTEP(2) QSTEP(3)
#undef QSTEP
    }
    pin(acc);
#pragma unroll
    for (int i = 0; i < 32; i++) Q[i] = pack2(acc[2 * i], acc[2 * i + 1]);
  }
  TSC(6); TG(122);
  float S[64];
  uint32_t P[32];
  Soft f = {0.f, 0.f, 0.f, 0.f, 0u};
  mbar_spin(FULLB(1), 0);
  TURN_BEGIN();
  pin(Q);
  wg_fence();
  tile_qk(S, Q, SDESC(1, 16));
  wg_commit();
  TURN_END();
  wg_wait<0>();
  pin(S);
  mbar_arrive_warp(EMPTYB(1));
  softmax_step(S, f);
#pragma unroll
  for (int i = 0; i < 32; i++) P[i] = pack2(S[2 * i], S[2 * i + 1]);
  mbar_spin(FULLB(2), 0);
#pragma unroll 1
  for (int j = 1; j < 16; j++) {
    const uint32_t st = (2 * j) & 3;
    TURN_BEGIN();
    pin(Q); pin(P);
    wg_fence();
    tile_qk(S, Q, SDESC(st, 16));
    wg_commit();
    pin(acc);
    if ((j & 3) == 1 && j != 1) {
      scale_acc(acc, f.i0, f.i1);
      stash_acc(acc, stash + ((j >> 2) - 1) * 16384);
    }
    pin(acc);
    mbar_spin(FULLB(st + 1), (j >> 1) & 1);
    wg_fence();
    tile_rs_mn<8, 0, 2>(acc, P, SDESC(st + 1, 16384), (j & 3) != 1);
    wg_commit();
    TURN_END();
    if ((j & 3) == 0) head_end(f);
    wg_wait<1>();
    pin(S);
    mbar_arrive_warp(EMPTYB(st));
    softmax_step(S, f);
    pin(S);
    if ((j & 3) == 3 && j != 15) {
#pragma unroll
      for (int i = 0; i < 8; i++) lds128(stash + (j >> 2) * 16384 + i * 2048, Q[4 * i], Q[4 * i + 1], Q[4 * i + 2], Q[4 * i + 3]);
    }
    mbar_spin(FULLB(st ^ 2), ((j + 1) >> 1) & 1);
    wg_wait<0>();
    mbar_arrive_warp(EMPTYB(st + 1));
#pragma unroll
    for (int i = 0; i < 32; i++) P[i] = pack2(S[2 * i], S[2 * i + 1]);
    if (!(j & 1)) TSC(23 + (j >> 1));
  }
  TURN_BEGIN();
  pin(P); pin(acc);
  wg_fence();
  tile_rs_mn<8, 0, 1>(acc, P, SDESC(0, 16384));
  wg_commit();
  TURN_END();
  head_end(f);
  const float i0 = f.i0, i1 = f.i1;
#pragma unroll
  for (int i = 0; i < 16; i++) lds128(stash + i * 2048, AO[4 * i], AO[4 * i + 1], AO[4 * i + 2], AO[4 * i + 3]);
  wg_wait<0>();
#pragma unroll
  for (int i = 16; i < 24; i++) lds128(stash + i * 2048, AO[4 * i], AO[4 * i + 1], AO[4 * i + 2], AO[4 * i + 3]);
  pin(acc);
  mbar_arrive_warp(EMPTYB(0));
#pragma unroll
  for (int i = 0; i < 16; i++) {
    AO[96 + 2 * i] = pack2(acc[4 * i] * i0, acc[4 * i + 1] * i0);
    AO[96 + 2 * i + 1] = pack2(acc[4 * i + 2] * i1, acc[4 * i + 3] * i1);
  }
  if (__builtin_expect(__any_sync(0xffffffffu, f.bad), 0)) {
    __align__(16) uint32_t tmp[128];
    slow_heads(p, tmp, row0, g, sb);
#pragma unroll
    for (int i = 0; i < 128; i++) AO[i] = tmp[i];
  }
}

__device__ __forceinline__ uint32_t a2_tags(const uint32_t (&a)[16], uint32_t t) { return lop3<0x80>(lop3<0x80>(a[0], a[4], a[8]), a[12], t); }
__device__ __forceinline__ void fetch_a2(uint32_t (&a)[16], const uint4* src) {
#pragma unroll
  for (int i = 0; i < 4; i++) {
    const uint4 v = ldg_b128(src + i * 32);
    a[4 * i] = v.x; a[4 * i + 1] = v.y; a[4 * i + 2] = v.z; a[4 * i + 3] = v.w;
  }
}
__device__ __forceinline__ void check_a2(uint32_t (&a)[16], uint32_t (&b)[16], const uint4* src) {
  uint32_t it = 0;
#pragma unroll 1
  while (!__all_sync(0xffffffffu, a2_tags(a, a2_tags(b, 1))) && ++it < SPIN_LIMIT) { fetch_a2(a, src); fetch_a2(b, src + 1024); }
}
__device__ __forceinline__ void load_a2(const uint4* a2w, const int kt, uint32_t (&a)[16], uint32_t lin, const uint32_t sb) {
  mbar_spin(sb + MB_A2 + 8 * kt, 0);
#pragma unroll
  for (int i = 0; i < 4; i++) lds128(SLOT(kt & 3) + lin + i * 512, a[4 * i], a[4 * i + 1], a[4 * i + 2], a[4 * i + 3]);
  uint32_t it = 0;
#pragma unroll 1
  while (!__all_sync(0xffffffffu, a2_tags(a, 1)) && ++it < SPIN_LIMIT) fetch_a2(a, a2w + kt * 1024);
}
template <int FIRST>
__device__ __forceinline__ void tile_ffn1(float (&Z0)[64], float (&Z1)[48], const uint32_t (&a)[16], uint64_t d) {
#pragma unroll
  for (int ks = 0; ks < 4; ks++) {
    if (FIRST == 0 && ks == 0) {
      wgmma_rs128_mn_init(Z0, a[0], a[1], a[2], a[3], d);
      wgmma_rs96_mn_init(Z1, a[0], a[1], a[2], a[3], d + 1024);
    } else {
      wgmma_rs128_mn_acc(Z0, a[4 * ks], a[4 * ks + 1], a[4 * ks + 2], a[4 * ks + 3], d + ks * 128);
      wgmma_rs96_mn_acc(Z1, a[4 * ks], a[4 * ks + 1], a[4 * ks + 2], a[4 * ks + 3], d + ks * 128 + 1024);
    }
  }
}

__device__ __forceinline__ uint4 add4(uint4 a, uint4 b) { return make_uint4(bf2_add(a.x, b.x), bf2_add(a.y, b.y), bf2_add(a.z, b.z), bf2_add(a.w, b.w)); }
__device__ __forceinline__ uint4 gate_add(uint4 x, uint32_t va, uint4 y) {
  uint32_t g0, g1;
  asm volatile("ld.shared.b32 %0, [%2];\nld.shared.b32 %1, [%2+16];" : "=r"(g0), "=r"(g1) : "r"(va) : "memory");
  return make_uint4(bf2_add(x.x, bf2_mul(g0, y.x)), bf2_add(x.y, bf2_mul(g0, y.y)), bf2_add(x.z, bf2_mul(g1, y.z)), bf2_add(x.w, bf2_mul(g1, y.w)));
}
__device__ __forceinline__ void write_out(uint4 y, uint32_t xa, uint32_t va, __nv_bfloat16* po) {
  uint4 v;
  ldsm4(xa, v.x, v.y, v.z, v.w);
  v = gate_add(v, va, y);
  stsm4(xa, v.x, v.y, v.z, v.w);
  __syncwarp();
  lds128(xa, v.x, v.y, v.z, v.w);
  stg128(po, v.x, v.y, v.z, v.w);
}
template <int TAG>
__device__ __forceinline__ void load4(uint4 (&u)[4], const uint4* src) {
#pragma unroll
  for (int i = 0; i < 4; i++) ldg_retry<TAG>(u[i].x, u[i].y, u[i].z, u[i].w, src + i * 128);
}
template <int TAG>
__device__ __forceinline__ uint32_t part_missing(const uint4 (&u)[4]) {
  return TAG ? lop3<0x2a>(lop3<0x80>(u[0].x, u[1].x, u[2].x), u[3].x, 1) : lop3<0xa8>(lop3<0xfe>(u[0].x, u[1].x, u[2].x), u[3].x, 1);
}

__device__ __forceinline__ void back(const Params& p, uint32_t (&A)[128], float (&acf)[64], const uint32_t tag, const int row0, const int wg,
                                     const int mb, const uint32_t sb) {
  float (&ac2)[32] = *reinterpret_cast<float(*)[32]>(&acf[0]);
  const int tid = threadIdx.x, warp = tid >> 5;
  const uint32_t lane = tid & 31;
  TSC(7); TG(123);
#define PAR(n) (((n) >> 2) & 1)
  const uint32_t olin = keep(warp * 2048 + lane * 16);
  const uint32_t rfull = sb + MB_RFULL + 8 * wg;
  uint4* dst = keep(p.s->part + ((mb >> 3) * 32 + warp) * 1024 + ((mb & 1) * 4 + ((mb & 7) >> 1)) * 128 + lane);
  pin(A);
  asm volatile("setmaxnreg.dec.sync.aligned.u32 216;");
  mbar_arrive_remote((sb + MB_CREDIT) ^ PEER);
  mbar_arrive_warp(sb + MB_GO);
  mbar_spin(sb + MB_CLR, 0);
  uint32_t kw[16], a0[16], a1[16];
#pragma unroll
  for (int i = 0; i < 16; i++) kw[i] = 0;
  const uint4* a2w = keep(p.s->a2 + (mb >> 3) * 8192 + warp * 128 + lane);
#pragma unroll 1
  for (int k = 0;; k++) {
    const uint32_t s0 = (2 * k + 1) & 3, s1 = (2 * k + 2) & 3;
    mbar_spin(FULLB(s0), (k >> 1) & 1);
    TURN_BEGIN();
    wg_fence();
    tile_rs64_mn<16, 0, 0>(ac2, A, SDESC(s0, 16));
    wg_commit();
    TURN_END();
    if (k & 1) {
      mbar_spin(sb + MB_CREDIT, (k >> 1) & 1);
      send_chunk(kw, SLOT(4) + olin, rfull + (k & 2) * 8);
    } else if (k) {
      mbar_spin(rfull + (~k & 2) * 8, ((k - 1) >> 2) & 1);
      keep_chunk<1>(kw, SLOT(4) + olin, dst, sb + MB_SENT + (k - 2) * 4);
      dst += 8192;
      mbar_arrive_remote((sb + MB_CREDIT) ^ PEER);
      TSC(7 + (k >> 1));
    }
    wg_wait<0>();
    mbar_arrive_warp(EMPTYB(s0));
    mbar_spin(FULLB(s1), ((k + 1) >> 1) & 1);
    TURN_BEGIN();
    wg_fence();
    tile_rs64_mn<16, 64, 1>(ac2, A, SDESC(s1, 16));
    wg_commit();
    TURN_END();
    if (k == 7) break;
    wg_wait<0>();
    mbar_arrive_warp(EMPTYB(s1));
    pin(ac2);
    pack_chunk<0>(ac2, kw);
  }
  load_a2(a2w, 0, a0, olin, sb);
  mbar_spin(rfull + 16, 1);
  wg_wait<0>();
  mbar_arrive_warp(EMPTYB(0));
  pin(ac2);
  pack_chunk<0>(ac2, kw);
  keep_chunk<1>(kw, SLOT(4) + olin, dst, sb + MB_SENT + 24);
  TSC(11); TG(124);
  uint32_t H[56];
  float acc[64];
  {
    float (&Z0)[64] = acc;
    float Z1[48];
#define F1ISSUE(KT, AR, FIRST)                                                       \
    TSC(31 + (KT));                                                                  \
    mbar_spin(FULLB(N_W1(KT) & 3), PAR(N_W1(KT)));                                   \
    TURN_BEGIN();                                                                    \
    pin(AR);                                                                         \
    wg_fence();                                                                      \
    tile_ffn1<FIRST>(Z0, Z1, AR, SDESC(N_W1(KT) & 3, 8192));                         \
    wg_commit();                                                                     \
    TURN_END();
#define F1DONE(KT)                                                                   \
    wg_wait<0>();                                                                    \
    mbar_arrive_warp(EMPTYB(N_W1(KT) & 3));
    uint32_t b0[16], b1[16];
    F1ISSUE(0, a0, 0) load_a2(a2w, 1, a1, olin, sb); F1DONE(0)
    F1ISSUE(1, a1, 1) load_a2(a2w, 2, a0, olin, sb); F1DONE(1)
    F1ISSUE(2, a0, 1)
    fetch_a2(b0, a2w + 4 * 1024); fetch_a2(b1, a2w + 5 * 1024);
    load_a2(a2w, 3, a1, olin, sb);
    mbar_arrive_warp(sb + MB_SLOTFREE);
    mbar_arrive_remote((sb + MB_CREDIT) ^ PEER);
    F1DONE(2)
    F1ISSUE(3, a1, 1) check_a2(b0, b1, a2w + 4 * 1024); F1DONE(3)
    F1ISSUE(4, b0, 1) F1DONE(4)
    fetch_a2(a0, a2w + 6 * 1024); fetch_a2(a1, a2w + 7 * 1024);
    F1ISSUE(5, b1, 1) check_a2(a0, a1, a2w + 6 * 1024); F1DONE(5)
#undef F1ISSUE
#undef F1DONE
    TSC(37);
    mbar_spin(FULLB(N_W1(6) & 3), PAR(N_W1(6)));
    mbar_spin(FULLB(N_W1(7) & 3), PAR(N_W1(7)));
    TURN_BEGIN();
    pin(a0); pin(a1);
    wg_fence();
    tile_rs_mn<4, 0, 1>(Z0, a0, SDESC(N_W1(6) & 3, 8192));
    tile_rs_mn<4, 0, 1>(Z0, a1, SDESC(N_W1(7) & 3, 8192));
    wg_commit();
    uint4 sta, stb;
    sta = ldg_ll(&p.s->st2[row0]); stb = ldg_ll(&p.s->st2[row0 + 8]);
#pragma unroll
    for (int ks = 0; ks < 8; ks++) {
      const uint32_t* a = ks < 4 ? &a0[4 * ks] : &a1[4 * (ks - 4)];
      wgmma_rs96_mn_acc(Z1, a[0], a[1], a[2], a[3], SDESC(N_W1(6 + (ks >> 2)) & 3, 8192) + (ks & 3) * 128 + 1024);
    }
    wg_commit();
    TURN_END();
    float hr0, nm0, hr1, nm1;
    poll_stats(&p.s->st2[row0], tag, sta, stb, hr0, nm0, hr1, nm1);
    mbar_spin(sb + MB_LATE, 0);
    wg_wait<1>();
    pin(Z0);
    TSC(13); TG(125);
    const uint32_t uvaddr = SLOT(3) + (lane & 3) * 16;
    silu_part<0>(Z0, H, uvaddr, hr0, nm0, hr1, nm1);
    pin(H);
    mbar_spin(FULLB(N_W2(0) & 3), PAR(N_W2(0)));
    wg_wait<0>();
    pin(Z1);
    mbar_arrive_warp(EMPTYB(N_W1(6) & 3));
    mbar_arrive_warp(EMPTYB(N_W1(7) & 3));
    TSC(38);
    TURN_BEGIN();
    wg_fence();
    tile_rs_mn<8, 0, 0>(acc, H, SDESC(N_W2(0) & 3, 16384));
    wg_commit();
    TURN_END();
    silu_part<8>(Z1, H, uvaddr, hr0, nm0, hr1, nm1);
    pin(H);
    mbar_spin(FULLB(N_W2(1) & 3), PAR(N_W2(1)));
    wg_wait<0>();
    mbar_arrive_warp(EMPTYB(N_W2(0) & 3));
  }
  TURN_BEGIN();
  wg_fence();
  tile_rs_mn<6, 32, 1>(acc, H, SDESC(N_W2(1) & 3, 16384));
  wg_commit();
  TURN_END();
  mbar_spin(sb + MB_CREDIT, 0);
  wg_wait<0>();
  mbar_arrive_warp(EMPTYB(N_W2(1) & 3));
  TSC(14);
  uint32_t ks[16], kk[16];
#pragma unroll 1
  for (int m = 0;; m++) {
    const uint32_t n = N_W2(2 * m + 2), rf = rfull + (m & 1) * 16, ob = SLOT((~m & 1) * 4) + olin;
    pin(acc);
    pack_chunk<0>(acc, ks);
    pack_chunk<32>(acc, kk);
    if (m == 3) break;
    PRB(1, 24);
    mbar_spin(FULLB(n & 3), PAR(n));
    PRB(1, 25);
    TURN_BEGIN();
    PRB(1, 26);
    wg_fence();
    tile_rs_mn<8, 0, 0>(acc, H, SDESC(n & 3, 16384));
    wg_commit();
    TURN_END();
    PRB(1, 27);
    send_chunk_bulk(ks, SLOT(1 + (m & 1)) + olin, ob, rf);
    PRB(1, 28);
    mbar_spin(FULLB((n + 1) & 3), PAR(n + 1));
    PRB(1, 29);
    wg_wait<0>();
    PRB(1, 30);
    mbar_arrive_warp(EMPTYB(n & 3));
    TURN_BEGIN();
    wg_fence();
    tile_rs_mn<6, 32, 1>(acc, H, SDESC((n + 1) & 3, 16384));
    wg_commit();
    if (m < 2 || wg == 0) TURN_END();
    PRB(1, 20);
    mbar_spin(rf, m >> 1);
    PRB(1, 21);
    keep_chunk<0>(kk, ob, dst - 3 * 8192, sb + MB_SENT + 32 + m * 8);
    dst += 8192;
    TSC(15 + m);
    wg_wait<0>();
    PRB(1, 12);
    mbar_arrive_warp(EMPTYB((n + 1) & 3));
  }
  send_chunk(ks, SLOT(0) + olin, rfull + 16);
  TSC(19);
  mbar_spin(rfull + 16, 1);
  keep_chunk<0>(kk, SLOT(0) + olin, dst - 3 * 8192, sb + MB_SENT + 56);
  TSC(18);
#undef PAR
  {
    const uint4* src = p.s->part + ((mb >> 3) * 32 + 24 + (mb & 7)) * 1024 + wg * 512 + (tid & 127);
    const int col = 384 + warp * 16;
    uint4 u[4];
#pragma unroll
    for (int i = 0; i < 4; i++) u[i] = ldg_b128(src + i * 128);
    uint32_t it = 0;
#pragma unroll 1
    while (__any_sync(0xffffffffu, part_missing<0>(u)) && ++it < SPIN_LIMIT) load4<0>(u, src);
    TSC(22);
    write_out(add4(add4(u[0], u[1]), add4(u[2], u[3])),
              SLOT(5) + (6 + wg) * 2048 + (lane & 15) * 128 + ((((warp & 3) * 2 + (lane >> 4)) ^ (lane & 7)) << 4),
              sb + SM_MODBUF + col * 2 + (lane & 3) * 4, p.out + (mb * 16 + (lane & 15)) * 512 + col + (lane >> 4) * 8);
    TSC(23); TG(126);
  }
  if ((tid & 127) == 0) TSDUMP(wg * 40, wg * 40 + 40);
  if (tid == 0) TSDUMP(120, 127);
}

__device__ __forceinline__ void consumer(const Params& p, const int mb, const uint32_t sb, const int wg) {
  const int tid = threadIdx.x;
  const int warp = tid >> 5;
  const uint32_t lane = tid & 31;
  const int t = mb >> 3, g = mb & 7;
  uint32_t tag;
  if (wg == 0) {
    const int kr = (mb & 3) * 128 + (tid >> 2);
    const __nv_bfloat16* wp = p.wmod + (size_t)kr * 3072 + (mb >> 2) * 32 + (tid & 3) * 8;
    uint4 w[4];
    float c[4], a[8] = {0.f, 0.f, 0.f, 0.f, 0.f, 0.f, 0.f, 0.f};
#pragma unroll
    for (int i = 0; i < 4; i++) { w[i] = ldg_nc(wp + i * 32 * 3072); c[i] = __bfloat162float(p.c[kr + i * 32]); }
    tag = ld_cnt(&p.s->epoch[blockIdx.x * 8]) + 1;
#pragma unroll
    for (int i = 0; i < 4; i++) {
      const float s = bf_round(__fdividef(c[i], 1.0f + __expf(-c[i])));
      a[0] = fmaf(s, bf_lo(w[i].x), a[0]); a[1] = fmaf(s, bf_hi(w[i].x), a[1]);
      a[2] = fmaf(s, bf_lo(w[i].y), a[2]); a[3] = fmaf(s, bf_hi(w[i].y), a[3]);
      a[4] = fmaf(s, bf_lo(w[i].z), a[4]); a[5] = fmaf(s, bf_hi(w[i].z), a[5]);
      a[6] = fmaf(s, bf_lo(w[i].w), a[6]); a[7] = fmaf(s, bf_hi(w[i].w), a[7]);
    }
    TSC(0);
    const bool u = lane & 16, v = lane & 8, x = lane & 4;
#pragma unroll
    for (int i = 0; i < 4; i++) a[i] = (u ? a[i + 4] : a[i]) + __shfl_xor_sync(0xffffffffu, u ? a[i] : a[i + 4], 16);
#pragma unroll
    for (int i = 0; i < 2; i++) a[i] = (v ? a[i + 2] : a[i]) + __shfl_xor_sync(0xffffffffu, v ? a[i] : a[i + 2], 8);
    a[0] = (x ? a[1] : a[0]) + __shfl_xor_sync(0xffffffffu, x ? a[0] : a[1], 4);
    asm volatile("st.shared.f32 [%0], %1;" ::"r"(sb + SM_MODBUF + ((lane & 3) * 8 + (lane >> 2)) * 16 + warp * 4), "f"(a[0]) : "memory");
    bar_sync(3, 128);
    uint32_t f[4];
    lds128(sb + SM_MODBUF + lane * 16, f[0], f[1], f[2], f[3]);
    const float sum = (__uint_as_float(f[0]) + __uint_as_float(f[1])) + (__uint_as_float(f[2]) + __uint_as_float(f[3]));
    if (warp == 0)
      asm volatile("st.relaxed.gpu.global.b32 [%0], %1;" ::"l"(&p.s->modp[(mb & 3) * 1024 + (mb >> 2) * 32 + lane]),
                   "r"((__float_as_uint(sum) & ~7u) | (tag & 7u)) : "memory");
  } else {
    const int row = mb * 16 + ((tid & 127) >> 3);
    uint4 xv[8];
#pragma unroll
    for (int i = 0; i < 8; i++) xv[i] = ldg_nc(p.x + row * 512 + i * 64 + (lane & 7) * 8);
    tag = ld_cnt(&p.s->epoch[blockIdx.x * 8]) + 1;
    float s0 = 0.f, s1 = 0.f, q0 = 0.f, q1 = 0.f;
#pragma unroll
    for (int i = 0; i < 8; i++) {
      const uint32_t w[4] = {xv[i].x, xv[i].y, xv[i].z, xv[i].w};
#pragma unroll
      for (int k = 0; k < 4; k++) {
        const float a = bf_lo(w[k]), b = bf_hi(w[k]);
        s0 += a; s1 += b;
        q0 = fmaf(a, a, q0); q1 = fmaf(b, b, q1);
      }
    }
    TSC(0);
    s0 += s1; q0 += q1;
#pragma unroll
    for (int o = 4; o; o >>= 1) { s0 += __shfl_xor_sync(0xffffffffu, s0, o); q0 += __shfl_xor_sync(0xffffffffu, q0, o); }
    s0 *= (1.0f / 512);
    float rstd, mbf;
    ln_scalars(s0, fmaxf(fmaf(-s0, s0, q0 * (1.0f / 512)), 0.f), rstd, mbf);
    const float o = (lane & 1) ? -mbf : rstd * SC;
    if ((lane & 7) < 2) stg_ll((uint2*)&p.s->st1[row] + (lane & 1), pack2(o, o), tag);
  }
  TSC(1);
  asm volatile("setmaxnreg.inc.sync.aligned.u32 224;");
  bar_sync(0, NTHREADS);
  if (wg == 1) bar_arrive(1, 256);
  const int row0 = t * 128 + warp * 16 + (lane >> 2);
  uint32_t A[128];
  float acc[64];
  front(p, A, acc, tag, row0, wg, g, sb);
  back(p, A, acc, tag, row0, wg, mb, sb);
}

enum { M_X, M_X6, M_WQ, M_K, M_V, M_WO, M_W1, M_W1H, M_W2A, M_W2B, M_XR, M_COUNT };
struct Maps { CUtensorMap m[M_COUNT]; };
__device__ __forceinline__ void producer(const Maps& tm, const int mb, const uint32_t sb) {
  const int g = mb & 7;
#pragma unroll 1
  for (int n = 2; n < N_W2(8); n++) {
    int m, c0 = 0, c1, c2 = 0, cnt = 1;
    uint32_t bytes = 32768;
    if (n < 17) {
      m = M_WQ; c1 = ((n - 1) & 3) * 128; c2 = (g * 4 + (((n + 3) >> 2) & 3)) * 2;
    } else if (n < 49) {
      const bool v = (n & 1) ? n != 17 : n == 48;
      m = v ? M_V : M_K; c1 = g * 2048 + 1536 + (((n >> 1) - v) & 3) * 128;
    } else if (n < N_W1(0)) {
      m = M_WO; c1 = g * 512 + ((n - 49) & 1) * 256; c2 = ((n - 49) >> 1) ^ (~g & 1);
    } else if (n < N_W2(0)) {
      m = M_W1; c0 = g * 224; c1 = (n - N_W1(0)) * 64; cnt = 4;
    } else {
      const int h = (n - N_W2(0)) & 1;
      m = M_W2A + h; c1 = g * 224 + h * 128; c2 = (n - N_W2(0) - h) ^ (~g & 1); cnt = 2; bytes = 32768 - h * 8192;
    }
    const int s = n & 3;
    if (n == GO_AT + 1) mbar_wait(sb + MB_GO, 0);
    mbar_wait(EMPTYB(s), ((n >> 2) & 1) ^ 1);
    mbar_expect_tx(FULLB(s), bytes);
#pragma unroll 1
    for (int i = 0; i < cnt; i++)
      tma3d(STAGE(s) + i * (cnt == 4 ? 8192 : 16384), &tm.m[m + (i == 3)], FULLB(s), cnt == 4 && i < 3 ? c0 + i * 64 : 0, c1,
            cnt == 4 ? (i == 3 ? g : 0) : c2 ^ i);
  }
}

__device__ __forceinline__ void prefetcher(const Params& p, const CUtensorMap* tmXr, const int mb, const uint32_t sb) {
  mbar_wait(sb + MB_GO, 0);
  __nanosleep(PFD1);
#pragma unroll 1
  for (int i = 0; i < 4; i++) l2_prefetch((const char*)p.wmod + (mb * 4 + i) * 6144 + 2048, 4096);
  __nanosleep(PFD2);
  l2_prefetch((const char*)p.w1 + mb * 14336, 14336);
  __nanosleep(PFD3);
  mbar_wait(sb + MB_CLR, 0);
  mbar_wait(sb + MB_GO, 1);
  mbar_expect_tx(sb + MB_XRES, 16384 + 2048);
  tma3d(SLOT(5), tmXr, sb + MB_XRES, 0, mb * 16, 0);
  bulk_load(sb + SM_MODBUF, p.s->vec, 1024, sb + MB_XRES);
  bulk_load(sb + SM_MODBUF + 1024, p.s->vec + 1024, 1024, sb + MB_XRES);
  mbar_wait(sb + MB_RED + 24, 0);
  mbar_wait(sb + MB_SLOTFREE, 0);
  mbar_expect_tx(sb + MB_LATE, 1024 + 1792);
  bulk_load(sb + SM_MODBUF, p.s->vec + 1536, 1024, sb + MB_LATE);
  bulk_load(SLOT(3), p.s->uv + (mb & 7) * 112, 1792, sb + MB_LATE);
}

__device__ __forceinline__ void gatherer(const Params& p, const int mb, const uint32_t sb) {
  const uint32_t lane = threadIdx.x & 31;
  const uint4* src = p.s->a2 + (mb >> 3) * 8192;
#pragma unroll 1
  for (int m = 0; m < 2; m++, src += 2048) {
    const uint32_t bar = sb + MB_A2 + 16 * m, dst = SLOT((2 * m) & 3);
    if (lane == 0) { mbar_expect_tx(bar, 16384); mbar_expect_tx(bar + 8, 16384); }
    mbar_wait(sb + MB_RED + 8 * m, 0);
    uint32_t it = 0;
    while (!__all_sync(0xffffffffu, ld_cnt((const unsigned*)(src + 1024 + lane * 32)) & 1) && ++it < SPIN_LIMIT) {}
    if (lane == 0) {
      bulk_load_mc(dst + (mb & 1) * 16384, src + (mb & 1) * 1024, 16384, bar + (mb & 1) * 8);
      TS(88 + m);
    }
  }
  if (lane == 0) TSDUMP(88, 92);
}

template <int TAG>
__device__ __forceinline__ void reduce_step(const uint4* src, uint4& y0, uint4& y1) {
  uint4 u[4], v[4];
#pragma unroll
  for (int i = 0; i < 4; i++) { u[i] = ldg_b128(src + i * 128); v[i] = ldg_b128(src + 512 + i * 128); }
  uint32_t it = 0;
#pragma unroll 1
  while (__any_sync(0xffffffffu, part_missing<TAG>(u) | part_missing<TAG>(v)) && ++it < SPIN_LIMIT) { load4<TAG>(u, src); load4<TAG>(v, src + 512); }
  y0 = add4(add4(u[0], u[1]), add4(u[2], u[3]));
  y1 = add4(add4(v[0], v[1]), add4(v[2], v[3]));
}

__device__ __forceinline__ void reducer(const Params& p, const int mb, const uint32_t tag, const uint32_t sb) {
  const int rt = threadIdx.x & 127, rw = rt >> 5;
  const uint32_t lane = rt & 31;
  const int row = mb * 16 + (lane >> 2);
  uint4* a2 = p.s->a2 + (mb >> 3) * 8192 + (mb & 7) * 128 + rt;
  mbar_wait(sb + MB_GO, 0);
  __nanosleep(8000);
#pragma unroll
  for (int k = 0; k < 8; k++) stg128(a2 + k * 1024, 0, 0, 0, 0);
  {
    uint4* o = p.s->part + (mb >> 3) * 32768 + ((mb & 1) * 4 + ((mb & 7) >> 1)) * 128 + rt;
#pragma unroll 1
    for (int k = 0; k < 32; k++, o += 1024) {
      stg128(o, 0, 0, 0, 0);
      __nanosleep(100);
    }
  }
  __syncwarp();
  if (lane == 0) {
    uint32_t it = 0;
    while ((int)(ld_cnt(p.s->cnt + 32) - tag * NHELP) < 0) {
      __nanosleep(1000);
      if (++it > SPIN_LIMIT) asm volatile("trap;");
    }
    asm volatile("fence.acq_rel.gpu;\nfence.proxy.async;" ::: "memory");
  }
  __syncwarp();
  mbar_arrive_warp(sb + MB_CLR);
  uint32_t np0, np1;
  {
    float r0, n0, r1, n1;
    poll_stats(&p.s->st1[row], tag, r0, n0, r1, n1);
    np0 = __float_as_uint(n0); np1 = __float_as_uint(n1);
  }
  bar_sync(6, 128);
  asm volatile("setmaxnreg.inc.sync.aligned.u32 56;");
  mbar_wait(sb + MB_XRES, 0);
  uint32_t va = sb + SM_MODBUF + rw * 32 + (lane & 3) * 4;
  const uint4* src = p.s->part + ((mb >> 3) * 32 + (mb & 7)) * 1024 + rt;
  uint32_t xa = SLOT(5) + (lane & 15) * 128 + (((rw * 2 + (lane >> 4)) ^ (lane & 7)) << 4);
  float s0 = 0.f, q0 = 0.f, s1 = 0.f, q1 = 0.f;
#pragma unroll 1
  for (int m = 0; m < 4; m++, a2 += 2048, va += 256, src += 8192, xa += 4096) {
    uint4 y[2];
    mbar_wait(sb + MB_SENT + 8 * m, 0);
    if (rt == 0) TS(80 + 2 * m);
    reduce_step<1>(src, y[0], y[1]);
#pragma unroll
    for (int c = 0; c < 2; c++) {
      uint4 xv;
      uint32_t c0, c1;
      ldsm4(xa + c * 2048, xv.x, xv.y, xv.z, xv.w);
      asm volatile("ld.shared.b32 %0, [%2];\nld.shared.b32 %1, [%2+16];" : "=r"(c0), "=r"(c1) : "r"(va + c * 128 + 1024) : "memory");
      xv = gate_add(xv, va + c * 128, y[c]);
      y[c] = make_uint4(bf2_add(xv.x, np0), bf2_add(xv.y, np1), bf2_add(xv.z, np0), bf2_add(xv.w, np1));
      stg_b128(a2 + c * 1024, bf2_mul(y[c].x, c0) | 1, bf2_mul(y[c].y, c0), bf2_mul(y[c].z, c1), bf2_mul(y[c].w, c1));
      stsm4(xa + c * 2048, xv.x, xv.y, xv.z, xv.w);
    }
    mbar_arrive_warp(sb + MB_RED + 8 * m);
    if (rt == 0) TS(81 + 2 * m);
#pragma unroll
    for (int c = 0; c < 2; c++) {
      const float a = bf_lo(y[c].x), b = bf_hi(y[c].x), d = bf_lo(y[c].z), e = bf_hi(y[c].z);
      const float f = bf_lo(y[c].y), g = bf_hi(y[c].y), h = bf_lo(y[c].w), i = bf_hi(y[c].w);
      s0 += (a + b) + (d + e);
      q0 = fmaf(a, a, fmaf(b, b, fmaf(d, d, fmaf(e, e, q0))));
      s1 += (f + g) + (h + i);
      q1 = fmaf(f, f, fmaf(g, g, fmaf(h, h, fmaf(i, i, q1))));
    }
  }
  {
    s0 = quad_sum(s0); q0 = quad_sum(q0); s1 = quad_sum(s1); q1 = quad_sum(q1);
    const float mine = (lane & 2) ? ((lane & 1) ? q1 : s1) : ((lane & 1) ? q0 : s0);
    mbar_wait(sb + MB_SLOTFREE, 0);
    asm volatile("st.shared.f32 [%0], %1;" ::"r"(sb + SM_STAT + lane * 16 + rw * 4), "f"(mine) : "memory");
    bar_sync(6, 128);
    {
      uint32_t w[4];
      lds128(sb + SM_STAT + lane * 16, w[0], w[1], w[2], w[3]);
      const float tot = ((__uint_as_float(w[0]) + __uint_as_float(w[1])) + (__uint_as_float(w[2]) + __uint_as_float(w[3]))) * (1.0f / 512);
      const float oth = __shfl_xor_sync(0xffffffffu, tot, 1);
      const float a = (lane & 1) ? oth : tot, b = (lane & 1) ? tot : oth, piv = -bf_lo((lane & 2) ? np1 : np0);
      float rs, mbf;
      ln_scalars(piv + a, fmaxf(fmaf(-a, a, b), 0.f), rs, mbf);
      rs *= 0.5f;
      if (rw == 0) stg_ll((uint2*)&p.s->st2[row + (lane & 2) * 4] + (lane & 1), __float_as_uint((lane & 1) ? (piv - mbf) * rs : rs), tag);
      if (rt == 0) TS(112);
    }
  }
  __nv_bfloat16* po = p.out + (mb * 16 + (lane & 15)) * 512 + rw * 16 + (lane >> 4) * 8;
  src -= 4 * 8192;
  xa -= 4 * 4096;
  va -= 4 * 256;
  mbar_wait(sb + MB_LATE, 0);
#pragma unroll 1
  for (int m = 0; m < 3; m++, po += 128, va += 256, src += 8192, xa += 4096) {
    uint4 y0, y1;
    mbar_wait(sb + MB_SENT + 32 + 8 * m, 0);
    if (rt == 0 && m == 2) TS(113);
    reduce_step<0>(src, y0, y1);
    write_out(y0, xa, va, po);
    write_out(y1, xa + 2048, va + 128, po + 64);
  }
  if (rt == 0) {
    p.s->epoch[blockIdx.x * 8] = tag;
    TS(114);
    TSDUMP(110, 115);
    TSDUMP(80, 88);
  }
}

__device__ __noinline__ void helper_cta(const Params& p, uint8_t* smem) {
  const int tid = threadIdx.x, hb = blockIdx.x;
  float* sc = (float*)smem;
  float* red = sc + 512;
  float* vec = red + 8 * 448 * 2;
  const uint32_t tag = *(volatile unsigned*)&p.s->epoch[hb * 8] + 1;
  for (int i = tid; i < 512; i += NTHREADS) {
    const float c = __bfloat162float(p.c[i]);
    sc[i] = bf_round(__fdividef(c, 1.0f + __expf(-c)));
  }
  __nanosleep(3000);
  __syncthreads();
  {
    const int v = tid & 63, rg = tid >> 6;
    float a[8] = {0.f, 0.f, 0.f, 0.f, 0.f, 0.f, 0.f, 0.f};
#pragma unroll 1
    for (int k0 = rg * 16; k0 < 512; k0 += 128) {
      uint4 w[16];
#pragma unroll
      for (int i = 0; i < 16; i++) w[i] = ldg_nc(p.wmod + (size_t)(k0 + i) * 3072 + 1024 + hb * 512 + v * 8);
#pragma unroll
      for (int i = 0; i < 16; i++) {
        const float s = sc[k0 + i];
        a[0] = fmaf(s, bf_lo(w[i].x), a[0]); a[1] = fmaf(s, bf_hi(w[i].x), a[1]);
        a[2] = fmaf(s, bf_lo(w[i].y), a[2]); a[3] = fmaf(s, bf_hi(w[i].y), a[3]);
        a[4] = fmaf(s, bf_lo(w[i].z), a[4]); a[5] = fmaf(s, bf_hi(w[i].z), a[5]);
        a[6] = fmaf(s, bf_lo(w[i].w), a[6]); a[7] = fmaf(s, bf_hi(w[i].w), a[7]);
      }
    }
#pragma unroll
    for (int i = 0; i < 8; i++) red[rg * 512 + v * 8 + i] = a[i];
  }
  __syncthreads();
  for (int i = tid; i < 512; i += NTHREADS) {
    float v = bf_round(((red[i] + red[512 + i]) + (red[1024 + i] + red[1536 + i])) + ((red[2048 + i] + red[2560 + i]) + (red[3072 + i] + red[3584 + i])));
    if (hb == 2) v += 1.0f;
    p.s->vec[hb * 512 + i] = __float2bfloat16_rn(v);
  }
  __syncthreads();
  if (tid == 0) { signal_cnt(p.s->cnt); wait_cnt(p.s->cnt, tag * NHELP); }
  __syncthreads();
  if (tid < 128) {
    const uint4 a = ldg_cg(p.s->vec + 512 + tid * 8);
    float* d = vec + tid * 8;
    d[0] = bf_lo(a.x); d[1] = bf_hi(a.x); d[2] = bf_lo(a.y); d[3] = bf_hi(a.y);
    d[4] = bf_lo(a.z); d[5] = bf_hi(a.z); d[6] = bf_lo(a.w); d[7] = bf_hi(a.w);
  }
  __syncthreads();
  if (tid < 448) {
    const int v = tid % 56, rg = tid / 56;
    float u[8] = {0.f, 0.f, 0.f, 0.f, 0.f, 0.f, 0.f, 0.f}, w2[8] = {0.f, 0.f, 0.f, 0.f, 0.f, 0.f, 0.f, 0.f};
#pragma unroll 1
    for (int k0 = rg * 16; k0 < 512; k0 += 128) {
      uint4 w[16];
#pragma unroll
      for (int i = 0; i < 16; i++) w[i] = ldg_nc(p.w1 + (size_t)(k0 + i) * 1792 + hb * 448 + v * 8);
#pragma unroll
      for (int i = 0; i < 16; i++) {
        const float sbv = vec[k0 + i], cbv = vec[512 + k0 + i];
        const float f[8] = {bf_lo(w[i].x), bf_hi(w[i].x), bf_lo(w[i].y), bf_hi(w[i].y), bf_lo(w[i].z), bf_hi(w[i].z), bf_lo(w[i].w), bf_hi(w[i].w)};
#pragma unroll
        for (int e = 0; e < 8; e++) { u[e] = fmaf(cbv, f[e], u[e]); w2[e] = fmaf(sbv, f[e], w2[e]); }
      }
    }
#pragma unroll
    for (int e = 0; e < 8; e++) { red[(rg * 448 + v * 8 + e) * 2] = u[e]; red[(rg * 448 + v * 8 + e) * 2 + 1] = w2[e]; }
  }
  __syncthreads();
  if (tid < 224) {
    float4 r = make_float4(0.f, 0.f, 0.f, 0.f);
#pragma unroll
    for (int k = 0; k < 8; k++) {
      const float4 a = *(const float4*)&red[(k * 448 + tid * 2) * 2];
      r.x += a.x; r.z += a.y; r.y += a.z; r.w += a.w;
    }
    r.z *= 0.5f; r.w *= 0.5f;
    p.s->uv[hb * 224 + tid] = r;
  }
  __syncthreads();
  if (tid == 0) {
    signal_cnt(p.s->cnt + 32);
    p.s->epoch[hb * 8] = tag;
    TS(1);
    TSDUMP(0, 2);
  }
}

template <int LO, int HI>
__device__ __forceinline__ void init_bars(const uint32_t sb) {
#pragma unroll
  for (int i = LO; i < HI; i++) {
    const uint32_t o = SM_MISC + 8 * i;
    const bool c8 = (o >= MB_EMPTY && o < MB_XFULL) || o == MB_GO || o >= MB_CREDIT;
    const bool c4 = o >= MB_RED || (o >= MB_RFULL && o < MB_XRES);
    mbar_init(sb + o, c8 ? 8 : c4 ? 4 : 1);
  }
  asm volatile("fence.mbarrier_init.release.cluster;" ::: "memory");
  fence_async_smem();
}

__global__ void __cluster_dims__(2, 1, 1) __launch_bounds__(NTHREADS, 1)
fused_block_kernel(const __grid_constant__ Params p, const __grid_constant__ Maps tm) {
  extern __shared__ __align__(1024) uint8_t smem_raw[];
  const uint32_t sb = __shfl_sync(0xffffffffu, (uint32_t)__cvta_generic_to_shared(smem_raw), 0);
  { const int wg = threadIdx.x >> 7; (void)wg; if (wg == 0) TS(39); TG(120); }
  if (blockIdx.x < NHELP) {
    if (threadIdx.x == 0) TS(0);
    helper_cta(p, smem_raw);
    return;
  }
  const int b = blockIdx.x & 127;
  const int mb = b;
  const int warp = __shfl_sync(0xffffffffu, threadIdx.x >> 5, 0);
  if (warp == 12) {
    if (elect_one()) {
      init_bars<0, 12>(sb);
      mbar_expect_tx(FULLB(1), 32768);
      tma3d(STAGE(1), &tm.m[M_WQ], FULLB(1), 0, 0, ((mb & 7) * 4 + 1) * 2);
      mbar_expect_tx(FULLB(0), 32768);
      mbar_expect_tx(sb + MB_XFULL, 98304);
    }
    __syncwarp();
    asm volatile("barrier.cluster.arrive.relaxed.aligned;\nbarrier.cluster.wait.aligned;" ::: "memory");
    if (elect_one()) {
      const int r = mb & 1, row = (mb >> 3) * 128 + r * 64;
      tma3d_mc(STAGE(0) + r * 16384, &tm.m[M_X], FULLB(0), 0, row, 0);
      tma3d_mc(sb + SM_STASH + r * 49152, &tm.m[M_X6], sb + MB_XFULL, 0, row, 2);
    }
    __syncwarp();
  } else {
    asm volatile("barrier.cluster.arrive.relaxed.aligned;" ::: "memory");
  }
  if ((warp >> 2) == 2) {
    asm volatile("setmaxnreg.dec.sync.aligned.u32 40;");
    const uint32_t tag = ld_cnt(&p.s->epoch[blockIdx.x * 8]) + 1;
    bar_sync(0, NTHREADS);
    reducer(p, mb, tag, sb);
  } else if (warp >= 12) {
    asm volatile("setmaxnreg.dec.sync.aligned.u32 24;");
    if (warp >= 14) {
      if (elect_one()) { if (warp == 14) init_bars<12, 26>(sb); else init_bars<26, NBARS>(sb); }
      bar_sync(0, NTHREADS);
      if (elect_one()) {
        if (warp == 15) prefetcher(p, &tm.m[M_XR], mb, sb);
        else mbar_wait(sb + MB_SENT + 56, 0);
      }
    } else if (warp == 13) {
      if ((threadIdx.x & 31) < M_COUNT) prefetch_tmap(&tm.m[threadIdx.x & 31]);
      bar_sync(0, NTHREADS);
      gatherer(p, mb, sb);
    } else {
      if (sb != SB + (blockIdx.x & 1) * PEER) asm volatile("trap;");
      bar_arrive(0, NTHREADS);
      if (elect_one()) producer(tm, mb, sb);
    }
  } else {
    consumer(p, mb, sb, warp >> 2);
  }
}

typedef CUresult (*EncodeFn)(CUtensorMap*, CUtensorMapDataType, cuuint32_t, void*, const cuuint64_t*, const cuuint64_t*,
                             const cuuint32_t*, const cuuint32_t*, CUtensorMapInterleave, CUtensorMapSwizzle,
                             CUtensorMapL2promotion, CUtensorMapFloatOOBfill);

void make_map3(EncodeFn enc, CUtensorMap* m, const void* ptr, int rows, int cols, int box_rows, int box_panels) {
  cuuint64_t dims[3] = {64, (cuuint64_t)rows, (cuuint64_t)(cols / 64)};
  cuuint64_t strides[2] = {(cuuint64_t)cols * 2, 128};
  cuuint32_t box[3] = {64, (cuuint32_t)box_rows, (cuuint32_t)box_panels};
  cuuint32_t es[3] = {1, 1, 1};
  enc(m, CU_TENSOR_MAP_DATA_TYPE_BFLOAT16, 3, const_cast<void*>(ptr), dims, strides, box, es, CU_TENSOR_MAP_INTERLEAVE_NONE,
      CU_TENSOR_MAP_SWIZZLE_128B, CU_TENSOR_MAP_L2_PROMOTION_L2_256B, CU_TENSOR_MAP_FLOAT_OOB_FILL_NONE);
}

}

extern "C" void kernel_launch(void* const* d_in, const int* in_sizes, int n_in, void* d_out, int out_size) {
  (void)in_sizes; (void)n_in; (void)out_size;
  void* fn = nullptr;
  cudaDriverEntryPointQueryResult qr;
  cudaGetDriverEntryPoint("cuTensorMapEncodeTiled", &fn, cudaEnableDefault, &qr);
  EncodeFn enc = (EncodeFn)fn;
  void* sp = nullptr;
  cudaGetSymbolAddress(&sp, g_scratch);
  Scratch* s = (Scratch*)sp;
  Maps tm;
  make_map3(enc, &tm.m[M_X], d_in[0], 2048, 512, 64, 2);
  make_map3(enc, &tm.m[M_X6], d_in[0], 2048, 512, 64, 6);
  make_map3(enc, &tm.m[M_XR], d_in[0], 2048, 512, 16, 8);
  make_map3(enc, &tm.m[M_K], d_in[1], 16384, 128, 128, 2);
  make_map3(enc, &tm.m[M_V], d_in[2], 16384, 128, 128, 2);
  make_map3(enc, &tm.m[M_WQ], d_in[3], 512, 4096, 128, 2);
  make_map3(enc, &tm.m[M_WO], d_in[4], 4096, 512, 256, 1);
  make_map3(enc, &tm.m[M_W2A], d_in[7], 1792, 512, 128, 1);
  make_map3(enc, &tm.m[M_W2B], d_in[7], 1792, 512, 96, 1);
  const cuuint32_t es[3] = {1, 1, 1};
  {
    cuuint64_t dims[3] = {1792, 512, 1};
    cuuint64_t strides[2] = {1792 * 2, 1792 * 2 * 512};
    cuuint32_t box[3] = {64, 64, 1};
    enc(&tm.m[M_W1], CU_TENSOR_MAP_DATA_TYPE_BFLOAT16, 3, d_in[6], dims, strides, box, es, CU_TENSOR_MAP_INTERLEAVE_NONE,
        CU_TENSOR_MAP_SWIZZLE_128B, CU_TENSOR_MAP_L2_PROMOTION_L2_256B, CU_TENSOR_MAP_FLOAT_OOB_FILL_NONE);
  }
  {
    cuuint64_t dims[3] = {32, 512, 8};
    cuuint64_t strides[2] = {1792 * 2, 224 * 2};
    cuuint32_t box[3] = {64, 64, 1};
    enc(&tm.m[M_W1H], CU_TENSOR_MAP_DATA_TYPE_BFLOAT16, 3, (char*)d_in[6] + 192 * 2, dims, strides, box, es, CU_TENSOR_MAP_INTERLEAVE_NONE,
        CU_TENSOR_MAP_SWIZZLE_128B, CU_TENSOR_MAP_L2_PROMOTION_L2_64B, CU_TENSOR_MAP_FLOAT_OOB_FILL_NONE);
  }
  Params p;
  p.x = (const __nv_bfloat16*)d_in[0];
  p.k = (const __nv_bfloat16*)d_in[1];
  p.v = (const __nv_bfloat16*)d_in[2];
  p.wq = (const __nv_bfloat16*)d_in[3];
  p.wo = (const __nv_bfloat16*)d_in[4];
  p.w1 = (const __nv_bfloat16*)d_in[6];
  p.w2 = (const __nv_bfloat16*)d_in[7];
  p.c = (const __nv_bfloat16*)d_in[8];
  p.wmod = (const __nv_bfloat16*)d_in[9];
  p.out = (__nv_bfloat16*)d_out;
  p.s = s;
  cudaFuncSetAttribute(fused_block_kernel, cudaFuncAttributeMaxDynamicSharedMemorySize, SM_TOTAL);
  fused_block_kernel<<<128 + NHELP, NTHREADS, SM_TOTAL>>>(p, tm);
}
```
